```python
import torch

def _softmax(x, axis=-1):
    return torch.softmax(x, dim=axis)

def _gelu(x):
    return torch.nn.functional.gelu(x, approximate='tanh')

def _silu(x):
    return torch.nn.functional.silu(x)

def _sigmoid(x):
    return torch.sigmoid(x)

def _layernorm(x, axis=-1, eps=1e-05):
    m = x.mean(dim=axis, keepdim=True)
    v = x.var(dim=axis, keepdim=True, unbiased=False)
    return (x - m) / torch.sqrt(v + eps)

def _scatter_add(tgt, idx, src, axis=0):
    return tgt.clone().index_add_(axis, idx, src)

def _segment_sum(src, seg, n):
    out = torch.zeros((n,) + src.shape[1:], dtype=src.dtype)
    return out.index_add_(0, seg, src)

def _pad(x, pw):
    flat = tuple((v for pair in reversed(pw) for v in pair))
    return torch.nn.functional.pad(x, flat)
kernel_name = 'parallel_sum__memory_aug_recurrent_mem_tr__glu_gated_bilinear__prompt'

def setup_inputs():

    _w = lambda a: (lambda t: t.to(torch.bfloat16) if t.is_floating_point() else t)(torch.as_tensor(a))

    def _A_setup():
        B, S, Dm = (1, 2048, 512)
        H, Dh = (32, 128)
        M, seg = (8, 32)
        seg = min(seg, S)
        S = S // seg * seg
        return {'x': _w((lambda *s: torch.randn(*s, dtype=torch.bfloat16) * 0.05)(B, S, Dm)), 'mem0': _w((lambda *s: torch.randn(*s, dtype=torch.bfloat16) * 0.2)(B, M, Dm)), 'Wq': _w((lambda *s: torch.randn(*s, dtype=torch.bfloat16) * 1.6)(Dm, H, Dh) * Dm ** (-0.5)), 'Wk': _w((lambda *s: torch.randn(*s, dtype=torch.bfloat16) * 1.6)(Dm, H, Dh) * Dm ** (-0.5)), 'Wv': _w((lambda *s: torch.randn(*s, dtype=torch.bfloat16) * 0.2)(Dm, H, Dh) * Dm ** (-0.5)), 'Wo': _w((lambda *s: torch.randn(*s, dtype=torch.bfloat16) * 0.2)(H, Dh, Dm) * (H * Dh) ** (-0.5)), 'seg_len': seg}
    _A_in = _A_setup()

    def _B_setup():
        B, S, D, F = (1, 2048, 512, 1376)
        return {'x': _w((lambda *s: torch.randn(*s, dtype=torch.bfloat16) * 0.05)(B, S, D)), 'w_gate': _w((lambda *s: torch.randn(*s, dtype=torch.bfloat16) * 0.2)(D, F) * D ** (-0.5)), 'w_up': _w((lambda *s: torch.randn(*s, dtype=torch.bfloat16) * 0.2)(D, F) * D ** (-0.5)), 'w_down': _w((lambda *s: torch.randn(*s, dtype=torch.bfloat16) * 0.2)(F, D) * F ** (-0.5))}
    _B_in = _B_setup()
    return {'A_x': _A_in['x'], 'A_mem0': _A_in['mem0'], 'A_Wq': _A_in['Wq'], 'A_Wk': _A_in['Wk'], 'A_Wv': _A_in['Wv'], 'A_Wo': _A_in['Wo'], 'A_seg_len': _A_in['seg_len'], 'B_x': _B_in['x'], 'B_w_gate': _B_in['w_gate'], 'B_w_up': _B_in['w_up'], 'B_w_down': _B_in['w_down']}

def reference(A_x, A_mem0, A_Wq, A_Wk, A_Wv, A_Wo, A_seg_len, B_x, B_w_gate, B_w_up, B_w_down):

    def _A_ref(x, mem0, Wq, Wk, Wv, Wo, seg_len):
        B, S, Dm = x.shape
        H, Dh = (Wq.shape[1], Wq.shape[2])
        M = mem0.shape[1]
        scale = Dh ** (-0.5)
        n_seg = S // seg_len
        L = M + seg_len
        idx = torch.arange(L)
        mask = (idx[:, None] < M) | (idx[:, None] >= idx[None, :])
        mem = mem0
        outs = []
        for s in range(n_seg):
            xs = x[:, s * seg_len:(s + 1) * seg_len, :].clone()
            h = torch.concatenate([mem, xs], axis=1)
            q = torch.einsum('btd,dhe->bhte', h, Wq)
            k = torch.einsum('btd,dhe->bhte', h, Wk)
            v = torch.einsum('btd,dhe->bhte', h, Wv)
            scores = torch.einsum('bhqe,bhke->bhqk', q, k) * scale
            scores = torch.where(mask[None, None], scores, -1000000000.0)
            p = _softmax(scores, axis=-1)
            o = torch.einsum('bhqk,bhke->bhqe', p, v)
            o = torch.einsum('bhte,hed->btd', o, Wo)
            mem = o[:, :M, :].clone()
            outs.append(o[:, M:, :])
        return torch.concatenate(outs, axis=1)

    def _B_ref(x, w_gate, w_up, w_down):
        g = torch.einsum('bsd,df->bsf', x, w_gate)
        u = torch.einsum('bsd,df->bsf', x, w_up)
        h = g * u
        return torch.einsum('bsf,fd->bsd', h, w_down)
    x = A_x
    xn = _layernorm(x, axis=-1)
    return x + _A_ref(xn, A_mem0, A_Wq, A_Wk, A_Wv, A_Wo, A_seg_len) + _B_ref(xn, B_w_gate, B_w_up, B_w_down)
```

```cpp
#include <cuda_runtime.h>
#include <cuda_bf16.h>
#include <cuda.h>
#include <stdint.h>

#define DEV __device__ __forceinline__

constexpr int SEQ = 2048, DM = 512, NH = 32, DH = 128, FF = 1376, NSEG = 64;
constexpr int NCTA = 132, NPAIR = 66, NTHREADS = 384;

__device__ __align__(1024) __nv_bfloat16 g_xn[SEQ * DM];
__device__ __align__(1024) __nv_bfloat16 g_kv[SEQ * 8192];
__device__ __align__(1024) __nv_bfloat16 g_o[SEQ * 4096];
__device__ __align__(1024) __nv_bfloat16 g_h[SEQ * FF];
__device__ __align__(1024) float g_acc[SEQ * DM];
__device__ __align__(1024) uint4 g_kvm[NSEG * NH * 2 * 32 * 4];
__device__ __align__(1024) uint4 g_mb1[4 * 64 * 64 * 8];
__device__ __align__(1024) uint4 g_mb2[4 * 64 * 8];
__device__ __align__(1024) unsigned g_probe[2048 + 64 * 32];

struct Sync {
    unsigned start;        unsigned p0[31];
    unsigned tick[4][2];   unsigned p1[24];
    unsigned task[4];      unsigned p2[28];
    unsigned chain_ready;  unsigned p3[31];
    unsigned ln[16];       unsigned p4[16];
    unsigned hc[16];       unsigned p5[16];
    unsigned kv[16][32];
    unsigned oc[16][16];
    unsigned acc[16][2];
    unsigned dc[16][2][8];
    unsigned prog[64][8];
};
__device__ __align__(1024) Sync g_sync;

enum { M_XN = 0, M_H, M_O, M_KVL, M_WQ, M_WK, M_WV, M_WG, M_WU, M_WD, M_WO, M_KVC, M_SKV, M_SO, M_SH, M_SOUT,
       M_CQ, M_CK, M_CV, M_COUNT };
struct __align__(64) Params {
    CUtensorMap m[M_COUNT];
    const __nv_bfloat16* x;
    const __nv_bfloat16* mem0;
    const __nv_bfloat16* w[4];
    __nv_bfloat16* out;
};

enum { T_A = 0, T_B = 1, T_C = 2, T_E = 3, T_D = 4, T_END = 7 };
#define NTASK 534
__constant__ uint2 c_tasks[NTASK] = {
    {0x08800000u,0u}, {0x08800100u,0u}, {0x08800200u,0u}, {0x08800300u,0u}, {0x08800400u,0u}, {0x08800500u,0u}, {0x08800600u,0u}, {0x08800700u,0u},
    {0x08800800u,0u}, {0x08800900u,0u}, {0x08800a00u,0u}, {0x08800b00u,0u}, {0x08800c00u,0u}, {0x08800d00u,0u}, {0x08800e00u,0u}, {0x08800f00u,0u},
    {0x08801000u,0u}, {0x08801100u,0u}, {0x08801200u,0u}, {0x08801300u,0u}, {0x08801400u,0u}, {0x08801500u,0u}, {0x08801600u,0u}, {0x08801700u,0u},
    {0x08801800u,0u}, {0x08801900u,0u}, {0x08801a00u,0u}, {0x08801b00u,0u}, {0x08801c00u,0u}, {0x08801d00u,0u}, {0x08801e00u,0u}, {0x08801f00u,0u},
    {0x00800020u,0u}, {0x00800120u,0u}, {0x00800220u,0u}, {0x00800320u,0u}, {0x00800420u,0u}, {0x00800520u,0u}, {0x00800620u,0u}, {0x00800720u,0u},
    {0x00800820u,0u}, {0x00800920u,0u}, {0x00800a20u,0u}, {0x00800b20u,0u}, {0x00800c20u,0u}, {0x00800d20u,0u}, {0x00800e20u,0u}, {0x00800f20u,0u},
    {0x00801020u,0u}, {0x00801120u,0u}, {0x00801220u,0u}, {0x00801320u,0u}, {0x00801420u,0u}, {0x00801520u,0u}, {0x00801620u,0u}, {0x00801720u,0u},
    {0x00801820u,0u}, {0x00801920u,0u}, {0x00801a20u,0u}, {0x00801b20u,0u}, {0x00801c20u,0u}, {0x00801d20u,0u}, {0x00801e20u,0u}, {0x00801f20u,0u},
    {0x00800040u,0u}, {0x00800140u,0u}, {0x00800240u,0u}, {0x00800340u,0u}, {0x00800440u,0u}, {0x00800540u,0u}, {0x00800640u,0u}, {0x00800740u,0u},
    {0x00800840u,0u}, {0x00800940u,0u}, {0x00800a40u,0u}, {0x00800b40u,0u}, {0x00800c40u,0u}, {0x00800d40u,0u}, {0x00800e40u,0u}, {0x00800f40u,0u},
    {0x00801040u,0u}, {0x00801140u,0u}, {0x00801240u,0u}, {0x00801340u,0u}, {0x00801440u,0u}, {0x00801540u,0u}, {0x00801640u,0u}, {0x00801740u,0u},
    {0x00801840u,0u}, {0x00801940u,0u}, {0x00801a40u,0u}, {0x00801b40u,0u}, {0x00801c40u,0u}, {0x00801d40u,0u}, {0x00801e40u,0u}, {0x00801f40u,0u},
    {0x00800060u,0u}, {0x00800160u,0u}, {0x00800260u,0u}, {0x00800360u,0u}, {0x00800460u,0u}, {0x00800560u,0u}, {0x00800660u,0u}, {0x00800760u,0u},
    {0x00800860u,0u}, {0x00800960u,0u}, {0x00800a60u,0u}, {0x00800b60u,0u}, {0x00800c60u,0u}, {0x00800d60u,0u}, {0x00800e60u,0u}, {0x00800f60u,0u},
    {0x00801060u,0u}, {0x00801160u,0u}, {0x00801260u,0u}, {0x00801360u,0u}, {0x00801460u,0u}, {0x00801560u,0u}, {0x00801660u,0u}, {0x00801760u,0u},
    {0x00801860u,0u}, {0x00801960u,0u}, {0x00801a60u,0u}, {0x00801b60u,0u}, {0x00801c60u,0u}, {0x00801d60u,0u}, {0x00801e60u,0u}, {0x00801f60u,0u},
    {0x00800080u,0u}, {0x00800180u,0u}, {0x00800280u,0u}, {0x00800380u,0u}, {0x00800480u,0u}, {0x00800580u,0u}, {0x00800680u,0u}, {0x00800780u,0u},
    {0x00800880u,0u}, {0x00800980u,0u}, {0x00800a80u,0u}, {0x00800b80u,0u}, {0x00800c80u,0u}, {0x00800d80u,0u}, {0x00800e80u,0u}, {0x00800f80u,0u},
    {0x00801080u,0u}, {0x00801180u,0u}, {0x00801280u,0u}, {0x00801380u,0u}, {0x00801480u,0u}, {0x00801580u,0u}, {0x00801680u,0u}, {0x00801780u,0u},
    {0x00801880u,0u}, {0x00801980u,0u}, {0x00801a80u,0u}, {0x00801b80u,0u}, {0x00801c80u,0u}, {0x00801d80u,0u}, {0x00801e80u,0u}, {0x00801f80u,0u},
    {0x008000a0u,0u}, {0x008001a0u,0u}, {0x008002a0u,0u}, {0x008003a0u,0u}, {0x008004a0u,0u}, {0x008005a0u,0u}, {0x008006a0u,0u}, {0x008007a0u,0u},
    {0x008008a0u,0u}, {0x008009a0u,0u}, {0x00800aa0u,0u}, {0x00800ba0u,0u}, {0x00800ca0u,0u}, {0x00800da0u,0u}, {0x00800ea0u,0u}, {0x00800fa0u,0u},
    {0x008010a0u,0u}, {0x008011a0u,0u}, {0x008012a0u,0u}, {0x008013a0u,0u}, {0x008014a0u,0u}, {0x008015a0u,0u}, {0x008016a0u,0u}, {0x008017a0u,0u},
    {0x008018a0u,0u}, {0x008019a0u,0u}, {0x00801aa0u,0u}, {0x00801ba0u,0u}, {0x00801ca0u,0u}, {0x00801da0u,0u}, {0x00801ea0u,0u}, {0x00801fa0u,0u},
    {0x008000c0u,0u}, {0x008001c0u,0u}, {0x008002c0u,0u}, {0x008003c0u,0u}, {0x008004c0u,0u}, {0x008005c0u,0u}, {0x008006c0u,0u}, {0x008007c0u,0u},
    {0x008008c0u,0u}, {0x008009c0u,0u}, {0x00800ac0u,0u}, {0x00800bc0u,0u}, {0x00800cc0u,0u}, {0x00800dc0u,0u}, {0x00800ec0u,0u}, {0x00800fc0u,0u},
    {0x008010c0u,0u}, {0x008011c0u,0u}, {0x008012c0u,0u}, {0x008013c0u,0u}, {0x008014c0u,0u}, {0x008015c0u,0u}, {0x008016c0u,0u}, {0x008017c0u,0u},
    {0x008018c0u,0u}, {0x008019c0u,0u}, {0x00801ac0u,0u}, {0x00801bc0u,0u}, {0x00801cc0u,0u}, {0x00801dc0u,0u}, {0x00801ec0u,0u}, {0x00801fc0u,0u},
    {0x008000e0u,0u}, {0x008001e0u,0u}, {0x008002e0u,0u}, {0x008003e0u,0u}, {0x008004e0u,0u}, {0x008005e0u,0u}, {0x008006e0u,0u}, {0x008007e0u,0u},
    {0x008008e0u,0u}, {0x008009e0u,0u}, {0x00800ae0u,0u}, {0x00800be0u,0u}, {0x00800ce0u,0u}, {0x00800de0u,0u}, {0x00800ee0u,0u}, {0x00800fe0u,0u},
    {0x008010e0u,0u}, {0x008011e0u,0u}, {0x008012e0u,0u}, {0x008013e0u,0u}, {0x008014e0u,0u}, {0x008015e0u,0u}, {0x008016e0u,0u}, {0x008017e0u,0u},
    {0x008018e0u,0u}, {0x008019e0u,0u}, {0x00801ae0u,0u}, {0x00801be0u,0u}, {0x00801ce0u,0u}, {0x00801de0u,0u}, {0x00801ee0u,0u}, {0x00801fe0u,0u},
    {0x00800002u,0u}, {0x00800102u,0u}, {0x00800202u,0u}, {0x00800302u,0u}, {0x00800402u,0u}, {0x00800502u,0u}, {0x00800602u,0u}, {0x00800702u,0u},
    {0x00800802u,0u}, {0x00800902u,0u}, {0x00800a02u,0u}, {0x00800022u,0u}, {0x00800122u,0u}, {0x00800222u,0u}, {0x00800322u,0u}, {0x00800422u,0u},
    {0x00800522u,0u}, {0x00800622u,0u}, {0x00800722u,0u}, {0x00800822u,0u}, {0x00800922u,0u}, {0x00800a22u,0u}, {0x00800042u,0u}, {0x00800142u,0u},
    {0x00800242u,0u}, {0x00800342u,0u}, {0x00800442u,0u}, {0x00800542u,0u}, {0x00800642u,0u}, {0x00800742u,0u}, {0x00800842u,0u}, {0x00800942u,0u},
    {0x00800a42u,0u}, {0x00800062u,0u}, {0x00800162u,0u}, {0x00800262u,0u}, {0x00800362u,0u}, {0x00800462u,0u}, {0x00800562u,0u}, {0x00800662u,0u},
    {0x00800762u,0u}, {0x00800862u,0u}, {0x00800962u,0u}, {0x00800a62u,0u}, {0x00800082u,0u}, {0x00800182u,0u}, {0x00800282u,0u}, {0x00800382u,0u},
    {0x00800482u,0u}, {0x00800582u,0u}, {0x00800682u,0u}, {0x00800782u,0u}, {0x00800882u,0u}, {0x00800982u,0u}, {0x00800a82u,0u}, {0x008000a2u,0u},
    {0x008001a2u,0u}, {0x008002a2u,0u}, {0x008003a2u,0u}, {0x008004a2u,0u}, {0x008005a2u,0u}, {0x008006a2u,0u}, {0x008007a2u,0u}, {0x008008a2u,0u},
    {0x008009a2u,0u}, {0x00800aa2u,0u}, {0x008000c2u,0u}, {0x008001c2u,0u}, {0x008002c2u,0u}, {0x008003c2u,0u}, {0x008004c2u,0u}, {0x008005c2u,0u},
    {0x008006c2u,0u}, {0x008007c2u,0u}, {0x008008c2u,0u}, {0x008009c2u,0u}, {0x00800ac2u,0u}, {0x008000e2u,0u}, {0x008001e2u,0u}, {0x008002e2u,0u},
    {0x008003e2u,0u}, {0x008004e2u,0u}, {0x008005e2u,0u}, {0x008006e2u,0u}, {0x008007e2u,0u}, {0x008008e2u,0u}, {0x008009e2u,0u}, {0x00800ae2u,0u},
    {0x01600003u,0u}, {0x01600103u,0u}, {0x01600023u,0u}, {0x01600123u,0u}, {0x01600043u,0u}, {0x01600143u,0u}, {0x01600063u,0u}, {0x01600163u,0u},
    {0x01600083u,0u}, {0x01600183u,0u}, {0x016000a3u,0u}, {0x016001a3u,0u}, {0x016000c3u,0u}, {0x016001c3u,0u}, {0x016000e3u,0u}, {0x016001e3u,0u},
    {0x08800001u,0u}, {0x08800101u,0u}, {0x08800201u,0u}, {0x08800301u,0u}, {0x08800401u,0u}, {0x08800501u,0u}, {0x08800601u,0u}, {0x08800701u,0u},
    {0x08800801u,0u}, {0x08800901u,0u}, {0x08800a01u,0u}, {0x08800b01u,0u}, {0x08800c01u,0u}, {0x08800d01u,0u}, {0x08800e01u,0u}, {0x08800f01u,0u},
    {0x04000004u,0u}, {0x04000104u,0u}, {0x08800021u,0u}, {0x08800121u,0u}, {0x08800221u,0u}, {0x08800321u,0u}, {0x08800421u,0u}, {0x08800521u,0u},
    {0x08800621u,0u}, {0x08800721u,0u}, {0x08800821u,0u}, {0x08800921u,0u}, {0x08800a21u,0u}, {0x08800b21u,0u}, {0x08800c21u,0u}, {0x08800d21u,0u},
    {0x08800e21u,0u}, {0x08800f21u,0u}, {0x04000024u,0u}, {0x04000124u,0u}, {0x08800041u,0u}, {0x08800141u,0u}, {0x08800241u,0u}, {0x08800341u,0u},
    {0x08800441u,0u}, {0x08800541u,0u}, {0x08800641u,0u}, {0x08800741u,0u}, {0x08800841u,0u}, {0x08800941u,0u}, {0x08800a41u,0u}, {0x08800b41u,0u},
    {0x08800c41u,0u}, {0x08800d41u,0u}, {0x08800e41u,0u}, {0x08800f41u,0u}, {0x04000044u,0u}, {0x04000144u,0u}, {0x08800061u,0u}, {0x08800161u,0u},
    {0x08800261u,0u}, {0x08800361u,0u}, {0x08800461u,0u}, {0x08800561u,0u}, {0x08800661u,0u}, {0x08800761u,0u}, {0x08800861u,0u}, {0x08800961u,0u},
    {0x08800a61u,0u}, {0x08800b61u,0u}, {0x08800c61u,0u}, {0x08800d61u,0u}, {0x08800e61u,0u}, {0x08800f61u,0u}, {0x04000064u,0u}, {0x04000164u,0u},
    {0x08800081u,0u}, {0x08800181u,0u}, {0x08800281u,0u}, {0x08800381u,0u}, {0x08800481u,0u}, {0x08800581u,0u}, {0x08800681u,0u}, {0x08800781u,0u},
    {0x08800881u,0u}, {0x08800981u,0u}, {0x08800a81u,0u}, {0x08800b81u,0u}, {0x08800c81u,0u}, {0x08800d81u,0u}, {0x08800e81u,0u}, {0x08800f81u,0u},
    {0x04000084u,0u}, {0x04000184u,0u}, {0x088000a1u,0u}, {0x088001a1u,0u}, {0x088002a1u,0u}, {0x088003a1u,0u}, {0x088004a1u,0u}, {0x088005a1u,0u},
    {0x088006a1u,0u}, {0x088007a1u,0u}, {0x088008a1u,0u}, {0x088009a1u,0u}, {0x08800aa1u,0u}, {0x08800ba1u,0u}, {0x08800ca1u,0u}, {0x08800da1u,0u},
    {0x08800ea1u,0u}, {0x08800fa1u,0u}, {0x040000a4u,0u}, {0x040001a4u,0u}, {0x088000c1u,0u}, {0x088001c1u,0u}, {0x088002c1u,0u}, {0x088003c1u,0u},
    {0x088004c1u,0u}, {0x088005c1u,0u}, {0x088006c1u,0u}, {0x088007c1u,0u}, {0x088008c1u,0u}, {0x088009c1u,0u}, {0x08800ac1u,0u}, {0x08800bc1u,0u},
    {0x08800cc1u,0u}, {0x08800dc1u,0u}, {0x08800ec1u,0u}, {0x08800fc1u,0u}, {0x040000c4u,0u}, {0x040001c4u,0u}, {0x088000e1u,0u}, {0x088001e1u,0u},
    {0x088002e1u,0u}, {0x088003e1u,0u}, {0x088004e1u,0u}, {0x088005e1u,0u}, {0x088006e1u,0u}, {0x088007e1u,0u}, {0x088008e1u,0u}, {0x088009e1u,0u},
    {0x08800ae1u,0u}, {0x08800be1u,0u}, {0x08800ce1u,0u}, {0x08800de1u,0u}, {0x08800ee1u,0u}, {0x08800fe1u,0u}, {0x004000ecu,16u}, {0x004000fcu,16u},
    {0x004080ecu,16u}, {0x004080fcu,16u}, {0x004100ecu,16u}, {0x004100fcu,16u}, {0x004180ecu,16u}, {0x004180fcu,16u}, {0x004200ecu,16u}, {0x004200fcu,16u},
    {0x004280ecu,16u}, {0x004280fcu,16u}, {0x004300ecu,16u}, {0x004300fcu,16u}, {0x004380ecu,16u}, {0x004380fcu,16u}, {0x004400ecu,16u}, {0x004400fcu,16u},
    {0x004480ecu,16u}, {0x004480fcu,16u}, {0x004500ecu,16u}, {0x004500fcu,16u}, {0x004580ecu,16u}, {0x004580fcu,16u}, {0x004600ecu,16u}, {0x004600fcu,16u},
    {0x004680ecu,16u}, {0x004680fcu,16u}, {0x004700ecu,16u}, {0x004700fcu,16u}, {0x004780ecu,16u}, {0x004780fcu,16u},
};

constexpr int STAGE_BYTES = 49152, NSTAGE = 4;
constexpr int SM_STAGING = NSTAGE * STAGE_BYTES;
constexpr int SM_BAR = SM_STAGING + 32768;
constexpr int SMEM_BYTES = SM_BAR + 1024;
constexpr int B_FULL = SM_BAR, B_EMPTY = SM_BAR + 32, B_TFULL = SM_BAR + 64, B_TEMPTY = SM_BAR + 80, B_ROLE = SM_BAR + 96,
              B_WQ = SM_BAR + 104, B_WK = SM_BAR + 112, B_WV = SM_BAR + 120, B_WO = SM_BAR + 128, B_KV = SM_BAR + 136  ,
              B_S = SM_BAR + 168;
constexpr int S_TASK = SM_BAR + 256  , S_ROLE = SM_BAR + 272  , S_PROBE = SM_BAR + 288  ;
constexpr int C_WV = 0, C_WQ = 65536, C_WK = 131072, C_RING = SM_STAGING;
constexpr int C_MEM = 131072, C_QB = C_MEM + 10240, C_KB = C_QB + 2048, C_SB = C_KB + 2048, C_OB = C_SB + 2560;

#define SENT 0xFFFFFFFFu

DEV uint32_t smem_u32(const void* p) { return (uint32_t)__cvta_generic_to_shared(p); }
DEV uint32_t mapa(uint32_t a, uint32_t r) { uint32_t o; asm("mapa.shared::cluster.u32 %0, %1, %2;" : "=r"(o) : "r"(a), "r"(r)); return o; }
DEV void mbar_init(uint32_t a, uint32_t c) { asm volatile("mbarrier.init.shared::cta.b64 [%0], %1;" ::"r"(a), "r"(c) : "memory"); }
DEV void mbar_expect(uint32_t a, uint32_t b) { asm volatile("mbarrier.arrive.expect_tx.shared::cta.b64 _, [%0], %1;" ::"r"(a), "r"(b) : "memory"); }
DEV void mbar_arrive_cl(uint32_t a) { asm volatile("mbarrier.arrive.shared::cluster.b64 _, [%0];" ::"r"(a) : "memory"); }
DEV void mbar_expect_cl(uint32_t a, uint32_t b) { asm volatile("mbarrier.arrive.expect_tx.shared::cluster.b64 _, [%0], %1;" ::"r"(a), "r"(b) : "memory"); }
DEV void st_async_u2(uint32_t a, uint32_t x, uint32_t y, uint32_t bar) {
    asm volatile("st.async.weak.shared::cluster.mbarrier::complete_tx::bytes.v2.u32 [%0], {%1,%2}, [%3];" ::"r"(a), "r"(x), "r"(y), "r"(bar) : "memory");
}
DEV void bcast2(uint32_t slot, uint32_t bar, uint32_t x, uint32_t y) {
    const uint32_t rs = mapa(slot, 1), rb = mapa(bar, 1);
    mbar_expect_cl(rb, 8); st_async_u2(rs, x, y, rb);
    mbar_expect(bar, 8); st_async_u2(slot, x, y, bar);
}
DEV bool mbar_try(uint32_t a, uint32_t par) {
    uint32_t ok;
    asm volatile("{ .reg .pred p; mbarrier.try_wait.parity.shared::cta.b64 p, [%1], %2; selp.u32 %0, 1, 0, p; }" : "=r"(ok) : "r"(a), "r"(par) : "memory");
    return ok;
}
DEV bool mbar_try_cl(uint32_t a, uint32_t par) {
    uint32_t ok;
    asm volatile("{ .reg .pred p; mbarrier.try_wait.parity.acquire.cluster.shared::cta.b64 p, [%1], %2; selp.u32 %0, 1, 0, p; }" : "=r"(ok) : "r"(a), "r"(par) : "memory");
    return ok;
}
constexpr long long TIMEOUT = 1000000000LL;
DEV void mbar_wait_slow(uint32_t a, uint32_t par) {
    long long t0 = clock64();
    while (!mbar_try_cl(a, par)) { if (clock64() - t0 > TIMEOUT) __trap(); }
}
DEV void mbar_wait(uint32_t a, uint32_t par) { if (!mbar_try(a, par)) { if (!mbar_try(a, par)) mbar_wait_slow(a, par); } }
DEV void mbar_wait_cl(uint32_t a, uint32_t par) { if (!mbar_try_cl(a, par)) mbar_wait_slow(a, par); }
DEV void bar_sync(int id, int n) { asm volatile("bar.sync %0, %1;" ::"r"(id), "r"(n) : "memory"); }
DEV void bar_arrive(int id, int n) { asm volatile("bar.arrive %0, %1;" ::"r"(id), "r"(n) : "memory"); }
DEV void cluster_arrive() { asm volatile("barrier.cluster.arrive.release.aligned;" ::: "memory"); }
DEV void cluster_wait() { asm volatile("barrier.cluster.wait.acquire.aligned;" ::: "memory"); }
DEV void fence_async_smem() { asm volatile("fence.proxy.async.shared::cta;" ::: "memory"); }
DEV void fence_async_all() { asm volatile("fence.proxy.async;" ::: "memory"); }
DEV void fence_gpu() { asm volatile("fence.acq_rel.gpu;" ::: "memory"); }

DEV unsigned ld_acq(const unsigned* p) { unsigned v; asm volatile("ld.acquire.gpu.global.u32 %0, [%1];" : "=r"(v) : "l"(p) : "memory"); return v; }
DEV unsigned ld_rlx(const unsigned* p) { unsigned v; asm volatile("ld.relaxed.gpu.global.u32 %0, [%1];" : "=r"(v) : "l"(p) : "memory"); return v; }
DEV void red_add(unsigned* p, unsigned v) { asm volatile("red.relaxed.gpu.global.add.u32 [%0], %1;" ::"l"(p), "r"(v) : "memory"); }
DEV void st_rlx(unsigned* p, unsigned v) { asm volatile("st.relaxed.gpu.global.u32 [%0], %1;" ::"l"(p), "r"(v) : "memory"); }
DEV uint4 ld_rlx4(const void* p) {
    uint4 v;
    asm volatile("ld.relaxed.gpu.global.v4.u32 {%0,%1,%2,%3}, [%4];" : "=r"(v.x), "=r"(v.y), "=r"(v.z), "=r"(v.w) : "l"(p) : "memory");
    return v;
}
DEV float2 ld_rlx_f2(const float* p) {
    float2 v;
    asm volatile("ld.relaxed.gpu.global.v2.f32 {%0,%1}, [%2];" : "=f"(v.x), "=f"(v.y) : "l"(p) : "memory");
    return v;
}
DEV void st_rlx4(void* p, uint4 v) { asm volatile("st.relaxed.gpu.global.v4.u32 [%0], {%1,%2,%3,%4};" ::"l"(p), "r"(v.x), "r"(v.y), "r"(v.z), "r"(v.w) : "memory"); }
DEV void st_rlx2(void* p, unsigned a, unsigned b) { asm volatile("st.relaxed.gpu.global.v2.u32 [%0], {%1,%2};" ::"l"(p), "r"(a), "r"(b) : "memory"); }
DEV void wait_cnt_slow(const unsigned* p, unsigned tgt) {
    long long t0 = clock64();
    while ((int)(ld_acq(p) - tgt) < 0) { __nanosleep(40); if (clock64() - t0 > TIMEOUT) __trap(); }
}
DEV void wait_cnt(const unsigned* p, unsigned tgt) { if ((int)(ld_acq(p) - tgt) < 0) wait_cnt_slow(p, tgt); }

DEV void tma2d(uint32_t dst, const CUtensorMap* m, int c0, int c1, uint32_t bar) {
    asm volatile("cp.async.bulk.tensor.2d.shared::cluster.global.tile.mbarrier::complete_tx::bytes [%0], [%1, {%3, %4}], [%2];"
                 ::"r"(dst), "l"(m), "r"(bar), "r"(c0), "r"(c1) : "memory");
}
DEV void tma2d_mc(uint32_t dst, const CUtensorMap* m, int c0, int c1, uint32_t bar) {
    asm volatile("cp.async.bulk.tensor.2d.shared::cluster.global.tile.mbarrier::complete_tx::bytes.multicast::cluster [%0], [%1, {%3, %4}], [%2], %5;"
                 ::"r"(dst), "l"(m), "r"(bar), "r"(c0), "r"(c1), "h"((unsigned short)3) : "memory");
}
DEV void tma4d(uint32_t dst, const CUtensorMap* m, int c0, int c1, int c2, int c3, uint32_t bar) {
    asm volatile("cp.async.bulk.tensor.4d.shared::cluster.global.tile.mbarrier::complete_tx::bytes [%0], [%1, {%3, %4, %5, %6}], [%2];"
                 ::"r"(dst), "l"(m), "r"(bar), "r"(c0), "r"(c1), "r"(c2), "r"(c3) : "memory");
}
DEV void tma_store(const CUtensorMap* m, int c0, int c1, uint32_t src) {
    asm volatile("cp.async.bulk.tensor.2d.global.shared::cta.tile.bulk_group [%0, {%2, %3}], [%1];" ::"l"(m), "r"(src), "r"(c0), "r"(c1) : "memory");
}
DEV void bulk_commit() { asm volatile("cp.async.bulk.commit_group;" ::: "memory"); }
template <int N> DEV void bulk_wait_read() { asm volatile("cp.async.bulk.wait_group.read %0;" ::"n"(N) : "memory"); }
DEV void bulk_wait_all() { asm volatile("cp.async.bulk.wait_group 0;" ::: "memory"); }
DEV void l2_prefetch(const void* p, uint32_t bytes) { asm volatile("cp.async.bulk.prefetch.L2.global [%0], %1;" ::"l"(p), "r"(bytes) : "memory"); }

DEV uint32_t pk(float lo, float hi) { uint32_t r; asm("cvt.rn.bf16x2.f32 %0, %1, %2;" : "=r"(r) : "f"(hi), "f"(lo)); return r; }
DEV uint32_t hadd2(uint32_t a, uint32_t b) { uint32_t r; asm("add.rn.bf16x2 %0, %1, %2;" : "=r"(r) : "r"(a), "r"(b)); return r; }
DEV uint32_t movm(uint32_t a) { uint32_t r; asm volatile("movmatrix.sync.aligned.m8n8.trans.b16 %0, %1;" : "=r"(r) : "r"(a)); return r; }
DEV float ex2(float x) { float r; asm("ex2.approx.ftz.f32 %0, %1;" : "=f"(r) : "f"(x)); return r; }
DEV void mma16(float* c, uint32_t a0, uint32_t a1, uint32_t a2, uint32_t a3, uint32_t b0, uint32_t b1) {
    asm volatile("mma.sync.aligned.m16n8k16.row.col.f32.bf16.bf16.f32 {%0,%1,%2,%3}, {%4,%5,%6,%7}, {%8,%9}, {%0,%1,%2,%3};"
                 : "+f"(c[0]), "+f"(c[1]), "+f"(c[2]), "+f"(c[3]) : "r"(a0), "r"(a1), "r"(a2), "r"(a3), "r"(b0), "r"(b1));
}
DEV void mma8(float* c, uint32_t a0, uint32_t a1, uint32_t b0) {
    asm volatile("mma.sync.aligned.m16n8k8.row.col.f32.bf16.bf16.f32 {%0,%1,%2,%3}, {%4,%5}, {%6}, {%0,%1,%2,%3};"
                 : "+f"(c[0]), "+f"(c[1]), "+f"(c[2]), "+f"(c[3]) : "r"(a0), "r"(a1), "r"(b0));
}
DEV void ldm4(uint32_t* r, uint32_t a) {
    asm volatile("ldmatrix.sync.aligned.m8n8.x4.shared.b16 {%0,%1,%2,%3}, [%4];" : "=r"(r[0]), "=r"(r[1]), "=r"(r[2]), "=r"(r[3]) : "r"(a) : "memory");
}
DEV void ldm4t(uint32_t* r, uint32_t a) {
    asm volatile("ldmatrix.sync.aligned.m8n8.x4.trans.shared.b16 {%0,%1,%2,%3}, [%4];" : "=r"(r[0]), "=r"(r[1]), "=r"(r[2]), "=r"(r[3]) : "r"(a) : "memory");
}
DEV void stm4(uint32_t a, uint32_t r0, uint32_t r1, uint32_t r2, uint32_t r3) {
    asm volatile("stmatrix.sync.aligned.m8n8.x4.shared.b16 [%0], {%1,%2,%3,%4};" ::"r"(a), "r"(r0), "r"(r1), "r"(r2), "r"(r3) : "memory");
}
DEV uint4 lds4(uint32_t a) { uint4 v; asm volatile("ld.shared.v4.u32 {%0,%1,%2,%3}, [%4];" : "=r"(v.x), "=r"(v.y), "=r"(v.z), "=r"(v.w) : "r"(a) : "memory"); return v; }
DEV float4 lds4f(uint32_t a) { float4 v; asm volatile("ld.shared.v4.f32 {%0,%1,%2,%3}, [%4];" : "=f"(v.x), "=f"(v.y), "=f"(v.z), "=f"(v.w) : "r"(a) : "memory"); return v; }
DEV uint32_t lds1(uint32_t a) { uint32_t v; asm volatile("ld.shared.u32 %0, [%1];" : "=r"(v) : "r"(a) : "memory"); return v; }
DEV void sts4(uint32_t a, uint4 v) { asm volatile("st.shared.v4.u32 [%0], {%1,%2,%3,%4};" ::"r"(a), "r"(v.x), "r"(v.y), "r"(v.z), "r"(v.w) : "memory"); }
DEV void sts2(uint32_t a, uint32_t x, uint32_t y) { asm volatile("st.shared.v2.u32 [%0], {%1,%2};" ::"r"(a), "r"(x), "r"(y) : "memory"); }
DEV void sts1(uint32_t a, uint32_t x) { asm volatile("st.shared.u32 [%0], %1;" ::"r"(a), "r"(x) : "memory"); }
DEV void sts_cl2(uint32_t a, uint32_t x, uint32_t y) { asm volatile("st.shared::cluster.v2.u32 [%0], {%1,%2};" ::"r"(a), "r"(x), "r"(y) : "memory"); }
DEV void st_async2(uint32_t a, float x, float y, uint32_t bar) {
    asm volatile("st.async.weak.shared::cluster.mbarrier::complete_tx::bytes.v2.f32 [%0], {%1,%2}, [%3];" ::"r"(a), "f"(x), "f"(y), "r"(bar) : "memory");
}
DEV void wg_fence() { asm volatile("wgmma.fence.sync.aligned;" ::: "memory"); }
DEV void wg_commit() { asm volatile("wgmma.commit_group.sync.aligned;" ::: "memory"); }
template <int N> DEV void wg_wait() { asm volatile("wgmma.wait_group.sync.aligned %0;" ::"n"(N) : "memory"); }
DEV uint64_t mkdesc(uint32_t addr, uint32_t lbo, uint32_t sbo, uint32_t sw) {
    return (uint64_t)((addr & 0x3FFFF) >> 4) | ((uint64_t)(lbo >> 4) << 16) | ((uint64_t)(sbo >> 4) << 32) | ((uint64_t)sw << 62);
}
#define R8(b) "+f"(d[b]), "+f"(d[b + 1]), "+f"(d[b + 2]), "+f"(d[b + 3]), "+f"(d[b + 4]), "+f"(d[b + 5]), "+f"(d[b + 6]), "+f"(d[b + 7])
DEV void wgmma256(float* d, uint64_t da, uint64_t db, int acc) {
    asm volatile(
        "{ .reg .pred p; setp.ne.b32 p, %130, 0;\n"
        "wgmma.mma_async.sync.aligned.m64n256k16.f32.bf16.bf16 {"
        "%0,%1,%2,%3,%4,%5,%6,%7,%8,%9,%10,%11,%12,%13,%14,%15,%16,%17,%18,%19,%20,%21,%22,%23,%24,%25,%26,%27,%28,%29,%30,%31,"
        "%32,%33,%34,%35,%36,%37,%38,%39,%40,%41,%42,%43,%44,%45,%46,%47,%48,%49,%50,%51,%52,%53,%54,%55,%56,%57,%58,%59,%60,%61,%62,%63,"
        "%64,%65,%66,%67,%68,%69,%70,%71,%72,%73,%74,%75,%76,%77,%78,%79,%80,%81,%82,%83,%84,%85,%86,%87,%88,%89,%90,%91,%92,%93,%94,%95,"
        "%96,%97,%98,%99,%100,%101,%102,%103,%104,%105,%106,%107,%108,%109,%110,%111,%112,%113,%114,%115,%116,%117,%118,%119,%120,%121,%122,%123,%124,%125,%126,%127"
        "}, %128, %129, p, 1, 1, 0, 1; }\n"
        : R8(0), R8(8), R8(16), R8(24), R8(32), R8(40), R8(48), R8(56), R8(64), R8(72), R8(80), R8(88), R8(96), R8(104), R8(112), R8(120)
        : "l"(da), "l"(db), "r"(acc));
}
DEV void wgmma8(float* d, uint64_t da, uint64_t db, int acc) {
    asm volatile("{ .reg .pred p; setp.ne.b32 p, %6, 0;\n"
                 "wgmma.mma_async.sync.aligned.m64n8k16.f32.bf16.bf16 {%0,%1,%2,%3}, %4, %5, p, 1, 1, 1, 0; }\n"
                 : "+f"(d[0]), "+f"(d[1]), "+f"(d[2]), "+f"(d[3]) : "l"(da), "l"(db), "r"(acc));
}

constexpr float SCALE_LOG2E = 0.08838834764831845f * 1.4426950408889634f;

DEV void chain_helper(const Params& P, uint32_t sb, int head, uint32_t rank, unsigned E, int warp, int lane) {
    const int g = lane >> 2, t = lane & 3;
    const int me = head * 2 + rank;
    const int tid = warp * 32 + lane;
    const int col0 = head * DH + rank * 64;
    if (tid == 0) {
        mbar_expect(sb + B_WQ, 65536);
        tma4d(sb + C_WQ, &P.m[M_CQ], col0, 0, 0, 0, sb + B_WQ);
        tma4d(sb + C_WQ + 32768, &P.m[M_CQ], col0, 0, 0, 8, sb + B_WQ);
        mbar_expect(sb + B_WK, 65536);
        tma4d(sb + C_WK, &P.m[M_CK], col0, 0, 0, 0, sb + B_WK);
        tma4d(sb + C_WK + 32768, &P.m[M_CK], col0, 0, 0, 8, sb + B_WK);
        mbar_expect(sb + B_WV, 65536);
        tma4d(sb + C_WV, &P.m[M_CV], col0, 0, 0, 0, sb + B_WV);
        tma4d(sb + C_WV + 32768, &P.m[M_CV], col0, 0, 0, 8, sb + B_WV);
    }
    {
        uint4 sv = make_uint4(SENT, SENT, SENT, SENT);
#pragma unroll 1
        for (int s = 0; s < 4; s++) {
            uint4* p = g_mb1 + (size_t)(s * 64 + me) * 512 + tid;
#pragma unroll
            for (int i = 0; i < 4; i++) st_rlx4(p + i * 128, sv);
        }
        if (tid < 32) st_rlx4(g_mb2 + ((tid >> 3) * 64 + me) * 8 + (tid & 7), sv);
        fence_gpu();
        bar_sync(5, 128);
        if (tid == 0) { fence_gpu(); red_add(&g_sync.chain_ready, 1); }
    }
    uint4 mv[4];
#pragma unroll
    for (int i = 0; i < 4; i++) {
        int r = warp * 16 + i * 4 + (lane >> 3), tok = lane & 7;
        const unsigned short* src = (const unsigned short*)P.mem0 + tok * DM + (r >> 2) * 32 + (r & 3) * 2;
        uint32_t w[4];
#pragma unroll
        for (int q = 0; q < 4; q++) {
            int gb = q >> 1, il = (q & 1) * 2;
            w[q] = (uint32_t)__ldg(src + il * 8 + gb) | ((uint32_t)__ldg(src + il * 8 + 8 + gb) << 16);
        }
        mv[i] = make_uint4(w[0], w[1], w[2], w[3]);
    }
    bar_sync(4, 384);
    const uint32_t memw = sb + C_MEM + (warp * 16 + (lane >> 3)) * 160 + (lane & 7) * 16;
#pragma unroll
    for (int i = 0; i < 4; i++) sts4(memw + i * 640, mv[i]);
    mbar_wait(sb + B_WV, 0);

    const uint32_t sel0 = g == 0 ? 0x00003f80u : (g == 2 ? 0x3f800000u : 0u);
    const uint32_t sel1 = g == 1 ? 0x00003f80u : (g == 3 ? 0x3f800000u : 0u);
    const uint32_t peer = rank ^ 1;
    const uint32_t s_self = sb + C_SB + warp * 512 + lane * 16 + rank * 8;
    const uint32_t s_peer = mapa(s_self, peer), bs_peer = mapa(sb + B_S, peer);
    const uint64_t da0 = mkdesc(sb + C_WV, 0, 1024, 1), db0 = mkdesc(sb + C_MEM, 160, 0, 0);
    const uint32_t koff = (warp * 8 + (lane & 7)) * 128;
    const uint32_t kx = lane & 7, kc = lane >> 3;
    const uint32_t vrow = lane & 15;
    const uint32_t voff = 4096 + vrow * 128 + (((2 * warp + (lane >> 4)) ^ (vrow & 7)) << 4);
    const char* g1p = (const char*)g_mb1 + (size_t)me * 8192 + ((g >> 1) * 4 + t) * 128 + (2 * warp + (g & 1)) * 16;
    char* g2w = (char*)g_mb2 + me * 128 + (2 * (2 * (warp & 1) + (g & 1)) + t) * 16 + (warp >> 1) * 8;
    const char* g2r = (const char*)g_mb2 + warp * 2048 + lane * 16;
    char* vexp = (char*)g_kvm + ((size_t)(head * 2 + 1) * 32 + lane) * 64 + rank * 32 + warp * 8;

#pragma unroll 1
    for (int s = 0; s < NSEG; s++) {
        fence_async_smem();
        bar_sync(1, 384);
        if (tid == 0 && s < NSEG - 1) mbar_expect(sb + B_S, 2560);
        float vac[4] = {0.f, 0.f, 0.f, 0.f};
        wg_fence();
#pragma unroll
        for (int k = 0; k < 32; k++) wgmma8(vac, da0 + k * 128, db0 + k * 20, 1);
        wg_commit();
        if (s == NSEG - 1) {
            wg_wait<0>();
            st_rlx2(vexp + (size_t)s * (NH * 2 * 2048), pk(vac[0], vac[1]), pk(vac[2], vac[3]));
            bar_arrive(3, 384);
            break;
        }
        const uint32_t stg = sb + C_RING + (s & 3) * 8192;
        mbar_wait(sb + B_KV + (s & 3) * 8, (s >> 2) & 1);
        uint32_t kf[8], vf[8];
        ldm4(kf, stg + koff + ((kc ^ kx) << 4));
        ldm4(kf + 4, stg + koff + (((kc + 4) ^ kx) << 4));
        ldm4t(vf, stg + voff);
        ldm4t(vf + 4, stg + voff + 2048);
        bar_sync(2, 384);
        {
            float c0[4] = {0.f, 0.f, 0.f, 0.f}, c1[4] = {0.f, 0.f, 0.f, 0.f};
            uint4 q0 = lds4(sb + C_QB + lane * 16), q1 = lds4(sb + C_QB + 512 + lane * 16);
            uint4 q2 = lds4(sb + C_QB + 1024 + lane * 16), q3 = lds4(sb + C_QB + 1536 + lane * 16);
            mma16(c0, q0.x, q0.z, q0.y, q0.w, kf[0], kf[1]);
            mma16(c1, q1.x, q1.z, q1.y, q1.w, kf[2], kf[3]);
            mma16(c0, q2.x, q2.z, q2.y, q2.w, kf[4], kf[5]);
            mma16(c1, q3.x, q3.z, q3.y, q3.w, kf[6], kf[7]);
            float x = (c0[0] + c0[2]) + (c1[0] + c1[2]), y = (c0[1] + c0[3]) + (c1[1] + c1[3]);
            st_async2(s_peer, x, y, bs_peer);
            st_async2(s_self, x, y, sb + B_S);
        }
        mbar_wait(sb + B_S, s & 1);
        float p[10];
#pragma unroll
        for (int i = 0; i < 5; i++) {
            float4 v = lds4f(sb + C_SB + i * 512 + lane * 16);
            p[2 * i] = v.x + v.z; p[2 * i + 1] = v.y + v.w;
        }
        float m = fmaxf(fmaxf(fmaxf(p[0], p[1]), fmaxf(p[2], p[3])), fmaxf(fmaxf(p[4], p[5]), fmaxf(p[6], p[7])));
        m = fmaxf(m, fmaxf(p[8], p[9]));
        m = fmaxf(m, __shfl_xor_sync(~0u, m, 1));
        m = fmaxf(m, __shfl_xor_sync(~0u, m, 2));
        const float mb = -m * SCALE_LOG2E;
#pragma unroll
        for (int i = 0; i < 10; i++) p[i] = ex2(fmaf(p[i], SCALE_LOG2E, mb));
        uint32_t pa[5];
#pragma unroll
        for (int i = 0; i < 5; i++) pa[i] = pk(p[2 * i], p[2 * i + 1]);
        float o0[4] = {0.f, 0.f, 0.f, 0.f}, o1[4] = {0.f, 0.f, 0.f, 0.f}, o2[4] = {0.f, 0.f, 0.f, 0.f}, o3[4] = {0.f, 0.f, 0.f, 0.f};
        mma16(o0, pa[0], 0u, pa[1], 0u, vf[0], vf[1]);
        mma16(o1, pa[0], 0u, pa[1], 0u, vf[2], vf[3]);
        mma16(o2, pa[2], 0u, pa[3], 0u, vf[4], vf[5]);
        mma16(o3, pa[2], 0u, pa[3], 0u, vf[6], vf[7]);
        float sum = ((p[0] + p[1]) + (p[2] + p[3])) + ((p[4] + p[5]) + (p[6] + p[7])) + (p[8] + p[9]);
        sum += __shfl_xor_sync(~0u, sum, 1);
        sum += __shfl_xor_sync(~0u, sum, 2);
        wg_wait<0>();
        const uint32_t vm0 = pk(vac[0], vac[1]), vm1 = pk(vac[2], vac[3]);
        mma8(o0, pa[4], 0u, vm0);
        mma8(o1, pa[4], 0u, vm1);
        const float inv = __fdividef(1.f, sum);
        sts2(sb + C_OB + (warp >> 1) * 512 + lane * 16 + (warp & 1) * 8,
             pk((o0[0] + o2[0]) * inv, (o0[1] + o2[1]) * inv), pk((o1[0] + o3[0]) * inv, (o1[1] + o3[1]) * inv));
        st_rlx2(vexp + (size_t)s * (NH * 2 * 2048), vm0, vm1);
        bar_arrive(3, 384);
        {
            const char* pp = g1p + (size_t)(s & 3) * (64 * 8192);
            uint4 v[4];
#pragma unroll
            for (int i = 0; i < 4; i++) v[i] = ld_rlx4(pp + i * 2048);
            unsigned it = 0;
            while (true) {
                bool ok = v[0].x != SENT && v[1].x != SENT && v[2].x != SENT && v[3].x != SENT;
                if (__all_sync(~0u, ok)) break;
                if (++it > 4000000u) __trap();
#pragma unroll
                for (int i = 0; i < 4; i++) if (v[i].x == SENT) v[i] = ld_rlx4(pp + i * 2048);
            }
            float c0[4] = {0.f, 0.f, 0.f, 0.f}, c1[4] = {0.f, 0.f, 0.f, 0.f};
            mma16(c0, v[0].x, v[0].y, v[0].z, v[0].w, sel0, sel1);
            mma16(c1, v[1].x, v[1].y, v[1].z, v[1].w, sel0, sel1);
            mma16(c0, v[2].x, v[2].y, v[2].z, v[2].w, sel0, sel1);
            mma16(c1, v[3].x, v[3].y, v[3].z, v[3].w, sel0, sel1);
#pragma unroll
            for (int i = 0; i < 4; i++) c0[i] += c1[i];
#pragma unroll
            for (int i = 0; i < 4; i++) c0[i] += __shfl_xor_sync(~0u, c0[i], 8);
#pragma unroll
            for (int i = 0; i < 4; i++) c0[i] += __shfl_xor_sync(~0u, c0[i], 16);
            if (lane < 8 && t < 2) st_rlx2(g2w + (s & 3) * 8192, pk(c0[0], c0[2]), pk(c0[1], c0[3]));
        }
        {
            const char* pp = g2r + (s & 3) * 8192;
            uint4 v[4];
#pragma unroll
            for (int i = 0; i < 4; i++) v[i] = ld_rlx4(pp + i * 512);
            unsigned it = 0;
            while (true) {
                bool ok = true;
#pragma unroll
                for (int i = 0; i < 4; i++) ok = ok && v[i].x != SENT && v[i].z != SENT;
                if (__all_sync(~0u, ok)) break;
                if (++it > 4000000u) __trap();
#pragma unroll
                for (int i = 0; i < 4; i++) if (v[i].x == SENT || v[i].z == SENT) v[i] = ld_rlx4(pp + i * 512);
            }
#pragma unroll
            for (int i = 0; i < 4; i++) sts4(memw + i * 640, v[i]);
        }
    }
}

DEV void chain_compute(const Params& P, uint32_t sb, int head, uint32_t rank, unsigned E, int cw, int lane) {
    const int g = lane >> 2, t = lane & 3;
    const int me = head * 2 + rank;
    const int j = cw & 3, kh = cw >> 2;
    uint32_t wq[16][4], wk[16][4], wo[16][4];
    {
        const int m = lane >> 3, jr = lane & 7;
        const int kap0 = 256 * kh + 8 * (jr >> 1) + 2 * (m >> 1) + (jr & 1);
        const int ch = 2 * j + (m & 1);
        mbar_wait(sb + B_WQ, 0);
#pragma unroll
        for (int ks = 0; ks < 16; ks++) {
            int kap = kap0 + 32 * (ks >> 1) + 4 * (ks & 1);
            ldm4t(wq[ks], sb + C_WQ + kap * 128 + ((ch ^ (kap & 7)) << 4));
        }
        bar_sync(6, 256);
        if (cw == 0 && lane == 0) {
            mbar_expect(sb + B_WO, 65536);
#pragma unroll 1
            for (int b = 0; b < 8; b++) tma2d(sb + C_WQ + b * 8192, &P.m[M_WO], b * 64, head * DH + rank * 64, sb + B_WO);
        }
        mbar_wait(sb + B_WK, 0);
#pragma unroll
        for (int ks = 0; ks < 16; ks++) {
            int kap = kap0 + 32 * (ks >> 1) + 4 * (ks & 1);
            ldm4t(wk[ks], sb + C_WK + kap * 128 + ((ch ^ (kap & 7)) << 4));
        }
        bar_arrive(4, 384);
        mbar_wait(sb + B_WO, 0);
#pragma unroll
        for (int mt = 0; mt < 4; mt++)
#pragma unroll
            for (int ks = 0; ks < 4; ks++) {
                int e = 16 * ks + 8 * (m >> 1) + jr, c = 2 * mt + (m & 1);
                ldm4t(wo[mt * 4 + ks], sb + C_WQ + cw * 8192 + e * 128 + ((c ^ (e & 7)) << 4));
            }
    }
    int nfill = 0;
    if (cw == 1 && lane == 0) {
        wait_cnt(&g_sync.kv[0][head >> 1], (E + 1) * 8);
        wait_cnt(&g_sync.kv[0][16 + (head >> 1)], (E + 1) * 8);
        fence_async_all();
#pragma unroll 1
        for (; nfill < 4; nfill++) {
            mbar_expect(sb + B_KV + nfill * 8, 8192);
            tma2d(sb + C_RING + nfill * 8192, &P.m[M_KVC], head * DH + rank * 64, nfill * 32, sb + B_KV + nfill * 8);
            tma2d(sb + C_RING + nfill * 8192 + 4096, &P.m[M_KVC], 4096 + head * DH + rank * 64, nfill * 32, sb + B_KV + nfill * 8);
        }
    }
    if (lane == 0) wait_cnt(&g_sync.chain_ready, (E + 1) * 64);
    __syncwarp();

    const uint32_t mrd = sb + C_MEM + (32 * kh + t) * 160 + g * 16;
    const uint32_t qkw = sb + C_QB + j * 512 + lane * 16 + kh * 8;
    char* g1w = (char*)g_mb1 + ((size_t)(8 * cw + (g >> 1)) * 64 + me) * 128 + (lane & 7) * 16;

#pragma unroll 1
    for (int s = 0; s < NSEG; s++) {
        bar_sync(1, 384);
        float q[4] = {0.f, 0.f, 0.f, 0.f}, k[4] = {0.f, 0.f, 0.f, 0.f};
#pragma unroll
        for (int p = 0; p < 8; p++) {
            uint4 b = lds4(mrd + p * 640);
            mma16(q, wq[2 * p][0], wq[2 * p][1], wq[2 * p][2], wq[2 * p][3], b.x, b.y);
            mma16(k, wk[2 * p][0], wk[2 * p][1], wk[2 * p][2], wk[2 * p][3], b.x, b.y);
            mma16(q, wq[2 * p + 1][0], wq[2 * p + 1][1], wq[2 * p + 1][2], wq[2 * p + 1][3], b.z, b.w);
            mma16(k, wk[2 * p + 1][0], wk[2 * p + 1][1], wk[2 * p + 1][2], wk[2 * p + 1][3], b.z, b.w);
        }
        sts2(qkw, movm(pk(q[0], q[1])), movm(pk(q[2], q[3])));
        sts2(qkw + 2048, movm(pk(k[0], k[1])), movm(pk(k[2], k[3])));
        if (cw == 0) {
            bar_sync(2, (s == NSEG - 1) ? 256 : 384);
            float c0[4] = {0.f, 0.f, 0.f, 0.f}, c1[4] = {0.f, 0.f, 0.f, 0.f};
            uint32_t kb[8];
#pragma unroll
            for (int i = 0; i < 4; i++) {
                uint4 kk = lds4(sb + C_KB + i * 512 + lane * 16);
                uint4 qq = lds4(sb + C_QB + i * 512 + lane * 16);
                kb[2 * i] = hadd2(kk.x, kk.z); kb[2 * i + 1] = hadd2(kk.y, kk.w);
                mma16((i & 1) ? c1 : c0, qq.x, qq.z, qq.y, qq.w, kb[2 * i], kb[2 * i + 1]);
            }
            if (s < NSEG - 1) {
                float x = (c0[0] + c0[2]) + (c1[0] + c1[2]), y = (c0[1] + c0[3]) + (c1[1] + c1[3]);
                const uint32_t a = sb + C_SB + 4 * 512 + lane * 16 + rank * 8;
                st_async2(mapa(a, rank ^ 1), x, y, mapa(sb + B_S, rank ^ 1));
                st_async2(a, x, y, sb + B_S);
            }
            uint4* ke = g_kvm + ((size_t)((s * NH + head) * 2) * 32 + lane) * 4 + rank * 2;
            st_rlx4(ke, make_uint4(kb[0], kb[1], kb[2], kb[3]));
            st_rlx4(ke + 1, make_uint4(kb[4], kb[5], kb[6], kb[7]));
        } else {
            bar_arrive(2, (s == NSEG - 1) ? 256 : 384);
        }
        bar_sync(3, 384);
        if (s < NSEG - 1) {
            uint4 b0 = lds4(sb + C_OB + lane * 16), b1 = lds4(sb + C_OB + 512 + lane * 16);
            float a[4][4];
#pragma unroll
            for (int mt = 0; mt < 4; mt++) { a[mt][0] = a[mt][1] = a[mt][2] = a[mt][3] = 0.f; }
#pragma unroll
            for (int mt = 0; mt < 4; mt++) mma16(a[mt], wo[mt * 4][0], wo[mt * 4][1], wo[mt * 4][2], wo[mt * 4][3], b0.x, b0.y);
#pragma unroll
            for (int mt = 0; mt < 4; mt++) mma16(a[mt], wo[mt * 4 + 1][0], wo[mt * 4 + 1][1], wo[mt * 4 + 1][2], wo[mt * 4 + 1][3], b0.z, b0.w);
#pragma unroll
            for (int mt = 0; mt < 4; mt++) mma16(a[mt], wo[mt * 4 + 2][0], wo[mt * 4 + 2][1], wo[mt * 4 + 2][2], wo[mt * 4 + 2][3], b1.x, b1.y);
#pragma unroll
            for (int mt = 0; mt < 4; mt++) mma16(a[mt], wo[mt * 4 + 3][0], wo[mt * 4 + 3][1], wo[mt * 4 + 3][2], wo[mt * 4 + 3][3], b1.z, b1.w);
            char* d = g1w + (size_t)(s & 3) * (64 * 8192);
            st_rlx4(d, make_uint4(pk(a[0][0], a[0][1]), pk(a[0][2], a[0][3]), pk(a[1][0], a[1][1]), pk(a[1][2], a[1][3])));
            st_rlx4(d + 4 * 8192, make_uint4(pk(a[2][0], a[2][1]), pk(a[2][2], a[2][3]), pk(a[3][0], a[3][1]), pk(a[3][2], a[3][3])));
        }
        if (cw == 0) {
            fence_gpu();
            __syncwarp();
            if (lane == 0) st_rlx(&g_sync.prog[me][0], E * 64 + s + 1);
        } else if (cw == 1) {
            if (lane == 0) {
#pragma unroll 1
                while (nfill < NSEG - 1 && nfill <= s + 4) {
                    if ((nfill & 3) == 0) {
                        const unsigned *f0 = &g_sync.kv[nfill >> 2][head >> 1], *f1 = &g_sync.kv[nfill >> 2][16 + (head >> 1)];
                        if (nfill == s + 1) { wait_cnt(f0, (E + 1) * 8); wait_cnt(f1, (E + 1) * 8); }
                        else if ((int)(ld_acq(f0) - (E + 1) * 8) < 0 || (int)(ld_acq(f1) - (E + 1) * 8) < 0) break;
                        fence_async_all();
                    }
                    const uint32_t st = nfill & 3;
                    mbar_expect(sb + B_KV + st * 8, 8192);
                    tma2d(sb + C_RING + st * 8192, &P.m[M_KVC], head * DH + rank * 64, nfill * 32, sb + B_KV + st * 8);
                    tma2d(sb + C_RING + st * 8192 + 4096, &P.m[M_KVC], 4096 + head * DH + rank * 64, nfill * 32, sb + B_KV + st * 8);
                    nfill++;
                }
            }
            __syncwarp();
        } else if (s >= 1) {
            uint4 sv = make_uint4(SENT, SENT, SENT, SENT);
            if (cw < 6) {
                uint4* p = g_mb1 + (size_t)(((s - 1) & 3) * 64 + me) * 512 + (cw - 2) * 128 + lane;
#pragma unroll
                for (int i = 0; i < 4; i++) st_rlx4(p + i * 32, sv);
                fence_gpu();
            } else if (cw == 6 && s >= 2) {
                if (lane < 8) st_rlx4(g_mb2 + (((s - 2) & 3) * 64 + me) * 8 + lane, sv);
                fence_gpu();
            }
        }
    }
}

DEV void bulk_producer(const Params& P, uint32_t sb, uint32_t rank, unsigned E) {
    uint32_t st = 0, ph = 1;
    const uint32_t tempty0 = mapa(sb + B_TEMPTY, 0);
    unsigned* tick = &g_sync.task[E & 3];
#pragma unroll 1
    for (int n = 0;; n++) {
        uint2 tk;
        if (rank == 0) {
            unsigned t = atomicAdd(tick, 1);
            tk = t < NTASK ? c_tasks[t] : make_uint2(T_END, 0);
            mbar_wait_cl(sb + B_TEMPTY + (n & 1) * 8, ((n >> 1) & 1) ^ 1);
            bcast2(sb + S_TASK + (n & 1) * 8, sb + B_TFULL + (n & 1) * 8, tk.x, tk.y);
        } else {
            mbar_wait_cl(sb + B_TFULL + (n & 1) * 8, (n >> 1) & 1);
            tk.x = lds1(sb + S_TASK + (n & 1) * 8); tk.y = lds1(sb + S_TASK + (n & 1) * 8 + 4);
            mbar_arrive_cl(tempty0 + (n & 1) * 8);
        }
        const int type = tk.x & 7;
        if (type == T_END) break;
        const int shareA = (tk.x >> 3) & 1;
        const int blk = ((tk.x >> 4) & 15) + (shareA ? 0 : rank);
        const int nt = ((tk.x >> 8) & 31) + (shareA ? rank : 0);
        const int kb0 = (tk.x >> 13) & 127, nkb = (tk.x >> 20) & 127;
        const CUtensorMap *ma, *mb, *mb2;
        int bcol, bcol2;
        if (type == T_A) { ma = &P.m[M_XN]; mb = mb2 = &P.m[nt < 16 ? M_WK : M_WV]; bcol = (nt & 15) * 256; bcol2 = bcol + 128; }
        else if (type == T_B) { ma = &P.m[M_XN]; mb = mb2 = &P.m[M_WQ]; bcol = nt * 256; bcol2 = bcol + 128; }
        else if (type == T_C) { ma = &P.m[M_XN]; mb = &P.m[M_WG]; mb2 = &P.m[M_WU]; bcol = bcol2 = nt * 128; }
        else if (type == T_E) { ma = &P.m[M_H]; mb = mb2 = &P.m[M_WD]; bcol = nt * 256; bcol2 = bcol + 128; }
        else { ma = &P.m[M_O]; mb = mb2 = &P.m[M_WO]; bcol = nt * 256; bcol2 = bcol + 128; }
        if (!shareA && rank) { mb = mb2; bcol = bcol2; }
        if (type <= T_C) { wait_cnt(&g_sync.ln[blk], (E + 1) * 64); fence_async_all(); }
        else if (type == T_E) { wait_cnt(&g_sync.hc[blk], (E + 1) * 88); fence_async_all(); }
#pragma unroll 1
        for (int kb = kb0; kb < kb0 + nkb; kb++) {
            if (type == T_D && ((kb & 3) == 0 || kb == kb0)) { wait_cnt(&g_sync.oc[blk][kb >> 2], (E + 1) * 8); fence_async_all(); }
            mbar_wait_cl(sb + B_EMPTY + st * 8, ph);
            const uint32_t fb = sb + B_FULL + st * 8, sa = sb + st * STAGE_BYTES, sbb = sa + 16384;
            mbar_expect(fb, STAGE_BYTES);
            if (!shareA) {
                tma2d_mc(sbb + rank * 16384, mb, bcol, kb * 64, fb);
                tma2d_mc(sbb + rank * 16384 + 8192, mb, bcol + 64, kb * 64, fb);
                tma2d(sa, ma, kb * 64, blk * 128, fb);
                tma2d(sa + 8192, ma, kb * 64, blk * 128 + 64, fb);
            } else {
                tma2d_mc(sa + rank * 8192, ma, kb * 64, blk * 128 + rank * 64, fb);
                tma2d(sbb, mb, bcol, kb * 64, fb);
                tma2d(sbb + 8192, mb, bcol + 64, kb * 64, fb);
                tma2d(sbb + 16384, mb2, bcol2, kb * 64, fb);
                tma2d(sbb + 24576, mb2, bcol2 + 64, kb * 64, fb);
            }
            if (++st == NSTAGE) { st = 0; ph ^= 1; }
        }
        if (type == T_B) {
            wait_cnt(&g_sync.kv[blk][nt], (E + 1) * 8);
            wait_cnt(&g_sync.kv[blk][16 + nt], (E + 1) * 8);
            fence_async_all();
#pragma unroll 1
            for (int x = 0; x < 4; x++) {
                mbar_wait_cl(sb + B_EMPTY + st * 8, ph);
                const uint32_t fb = sb + B_FULL + st * 8, sa = sb + st * STAGE_BYTES;
                mbar_expect(fb, 32768);
                const int c = (x & 1) * 4096 + nt * 256 + (x >> 1) * 128;
                tma2d(sa, &P.m[M_KVL], c, blk * 128, fb);
                tma2d(sa + 8192, &P.m[M_KVL], c, blk * 128 + 64, fb);
                tma2d(sa + 16384, &P.m[M_KVL], c + 64, blk * 128, fb);
                tma2d(sa + 24576, &P.m[M_KVL], c + 64, blk * 128 + 64, fb);
                if (++st == NSTAGE) { st = 0; ph ^= 1; }
            }
        }
    }
}

DEV void flush_flag(unsigned*& pend, int lane) {
    if (lane == 0 && pend) {
        bulk_wait_all(); fence_async_all(); fence_gpu(); red_add(pend, 1);
        pend = nullptr;
    }
}
template <typename F>
DEV void store_box(F val, uint32_t slot, uint32_t soff, const CUtensorMap* m, int c0, int c1, int lane) {
    if (lane == 0) bulk_wait_read<1>();
    __syncwarp();
#pragma unroll
    for (int jj = 0; jj < 4; jj++)
        stm4(slot + (soff ^ (jj << 5)), val(8 * jj + 0), val(8 * jj + 2), val(8 * jj + 4), val(8 * jj + 6));
    fence_async_smem();
    __syncwarp();
    if (lane == 0) { tma_store(m, c0, c1, slot); bulk_commit(); }
}

DEV void bulk_consumer(const Params& P, uint32_t sb, uint32_t rank, unsigned E, int cw, int lane) {
    const int g = lane >> 2, t = lane & 3;
    uint32_t st = 0, ph = 0;
    const uint32_t tempty0 = mapa(sb + B_TEMPTY, 0);
    const uint32_t empty_a = mapa(sb + B_EMPTY, lane & 1);
    const uint64_t da0 = mkdesc(sb + (cw >> 2) * 8192, 16, 1024, 1), db0 = mkdesc(sb + 16384, 8192, 1024, 1);
    const uint32_t stg = sb + SM_STAGING + cw * 4096;
    const int srow = (lane & 7) + ((lane >> 3) & 1) * 8;
    const uint32_t soff = srow * 128 + (((lane >> 4) ^ (srow & 7)) << 4);
    unsigned* pend = nullptr;
#pragma unroll 1
    for (int n = 0;; n++) {
        float acc[128];
        mbar_wait_cl(sb + B_TFULL + (n & 1) * 8, (n >> 1) & 1);
        const uint32_t tx = lds1(sb + S_TASK + (n & 1) * 8), ty = lds1(sb + S_TASK + (n & 1) * 8 + 4);
        __syncwarp();
        if (lane == 0) mbar_arrive_cl(tempty0 + (n & 1) * 8);
        const int type = tx & 7;
        if (type == T_END) break;
        const int shareA = (tx >> 3) & 1;
        const int blk = ((tx >> 4) & 15) + (shareA ? 0 : rank);
        const int nt = ((tx >> 8) & 31) + (shareA ? rank : 0);
        const int nkb = (tx >> 20) & 127;
        const int urgent = (tx >> 27) & 1;
        uint32_t pst = 0;
#pragma unroll
        for (int i = 0; i < 128; i++) acc[i] = 0.f;
#pragma unroll 1
        for (int kb = 0; kb < nkb; kb++) {
            if (!mbar_try(sb + B_FULL + st * 8, ph)) {
                flush_flag(pend, lane);
                mbar_wait(sb + B_FULL + st * 8, ph);
            }
            wg_fence();
            const uint64_t da = da0 + st * (STAGE_BYTES >> 4), db = db0 + st * (STAGE_BYTES >> 4);
            wgmma256(acc, da, db, 1);
            wgmma256(acc, da + 2, db + 128, 1);
            wgmma256(acc, da + 4, db + 256, 1);
            wgmma256(acc, da + 6, db + 384, 1);
            wg_commit();
            if (kb > 0) {
                wg_wait<1>();
                if (lane < 2) mbar_arrive_cl(empty_a + pst * 8);
                if (kb == 2) flush_flag(pend, lane);
            }
            pst = st;
            if (++st == NSTAGE) { st = 0; ph ^= 1; }
        }
        wg_wait<0>();
        if (lane < 2) mbar_arrive_cl(empty_a + pst * 8);
        flush_flag(pend, lane);
        const int row0 = blk * 128 + cw * 16;
        if (type == T_B) {
            uint32_t qa[64];
#pragma unroll
            for (int i = 0; i < 64; i++) qa[i] = pk(acc[2 * i], acc[2 * i + 1]);
            const int hi = cw & 1, sl = cw >> 1, seg = blk * 4 + sl;
            if (lane < 4) wait_cnt(&g_sync.prog[nt * 4 + lane][0], E * 64 + seg + 1);
            __syncwarp();
            const int rd = sl * 32 + hi * 16, rf = sl * 32;
#pragma unroll
            for (int hh = 0; hh < 2; hh++) {
                const uint4* kvm = g_kvm + ((size_t)((seg * NH + nt * 2 + hh) * 2) * 32 + lane) * 4;
                float s[5][4];
#pragma unroll
                for (int i = 0; i < 5; i++) { s[i][0] = s[i][1] = s[i][2] = s[i][3] = 0.f; }
                {
                    uint4 km[4];
#pragma unroll
                    for (int i = 0; i < 4; i++) km[i] = ld_rlx4(kvm + i);
#pragma unroll
                    for (int i = 0; i < 4; i++) {
                        const uint32_t* q = qa + hh * 32 + i * 8;
                        mma16(s[0], q[0], q[1], q[2], q[3], km[i].x, km[i].y);
                        mma16(s[0], q[4], q[5], q[6], q[7], km[i].z, km[i].w);
                    }
                }
                uint4 vm[4];
#pragma unroll
                for (int i = 0; i < 4; i++) vm[i] = ld_rlx4(kvm + 128 + i);
                mbar_wait(sb + B_FULL + st * 8, ph);
                {
                    const uint32_t kbase = sb + st * STAGE_BYTES;
#pragma unroll
                    for (int tl = 0; tl < 4; tl++) {
                        if (tl < 2 || hi) {
                            const int R = (tl < 2 ? rd : rf) + (tl & 1) * 8 + (lane & 7);
#pragma unroll
                            for (int qq = 0; qq < 4; qq++) {
                                uint32_t kf[4];
                                ldm4(kf, kbase + (qq >> 1) * 16384 + R * 128 + (((((qq & 1) * 4) + (lane >> 3)) ^ (lane & 7)) << 4));
                                const uint32_t* q = qa + hh * 32 + qq * 8;
                                mma16(s[1 + tl], q[0], q[1], q[2], q[3], kf[0], kf[1]);
                                mma16(s[1 + tl], q[4], q[5], q[6], q[7], kf[2], kf[3]);
                            }
                        }
                    }
                }
                __syncwarp();
                if (lane < 2) mbar_arrive_cl(empty_a + st * 8);
                if (++st == NSTAGE) { st = 0; ph ^= 1; }
                const float NINF = __int_as_float(0xff800000);
                if (2 * t > g) { s[1][0] = NINF; s[2][2] = NINF; }
                if (2 * t + 1 > g) { s[1][1] = NINF; s[2][3] = NINF; }
                s[2][0] = NINF; s[2][1] = NINF;
                if (!hi) {
#pragma unroll
                    for (int i = 0; i < 4; i++) { s[3][i] = NINF; s[4][i] = NINF; }
                }
                float m0 = fmaxf(s[0][0], s[0][1]), m1 = fmaxf(s[0][2], s[0][3]);
#pragma unroll
                for (int i = 1; i < 5; i++) { m0 = fmaxf(m0, fmaxf(s[i][0], s[i][1])); m1 = fmaxf(m1, fmaxf(s[i][2], s[i][3])); }
                m0 = fmaxf(m0, __shfl_xor_sync(~0u, m0, 1)); m1 = fmaxf(m1, __shfl_xor_sync(~0u, m1, 1));
                m0 = fmaxf(m0, __shfl_xor_sync(~0u, m0, 2)); m1 = fmaxf(m1, __shfl_xor_sync(~0u, m1, 2));
                m0 *= -SCALE_LOG2E; m1 *= -SCALE_LOG2E;
                float l0 = 0.f, l1 = 0.f;
                uint32_t pa[5][2];
#pragma unroll
                for (int i = 0; i < 5; i++) {
                    float a = ex2(fmaf(s[i][0], SCALE_LOG2E, m0)), b = ex2(fmaf(s[i][1], SCALE_LOG2E, m0));
                    float c = ex2(fmaf(s[i][2], SCALE_LOG2E, m1)), d = ex2(fmaf(s[i][3], SCALE_LOG2E, m1));
                    l0 += a + b; l1 += c + d;
                    pa[i][0] = pk(a, b); pa[i][1] = pk(c, d);
                }
                l0 += __shfl_xor_sync(~0u, l0, 1); l1 += __shfl_xor_sync(~0u, l1, 1);
                l0 += __shfl_xor_sync(~0u, l0, 2); l1 += __shfl_xor_sync(~0u, l1, 2);
                l0 = __fdividef(1.f, l0); l1 = __fdividef(1.f, l1);
                float o[64];
#pragma unroll
                for (int i = 0; i < 64; i++) o[i] = 0.f;
#pragma unroll
                for (int i = 0; i < 4; i++) {
                    mma8(o + 16 * i, pa[0][0], pa[0][1], vm[i].x);
                    mma8(o + 16 * i + 4, pa[0][0], pa[0][1], vm[i].y);
                    mma8(o + 16 * i + 8, pa[0][0], pa[0][1], vm[i].z);
                    mma8(o + 16 * i + 12, pa[0][0], pa[0][1], vm[i].w);
                }
                mbar_wait(sb + B_FULL + st * 8, ph);
                {
                    const uint32_t vbase = sb + st * STAGE_BYTES;
#pragma unroll
                    for (int pass = 0; pass < 2; pass++) {
                        if (pass == 0 || hi) {
                            const int R = (pass == 0 ? rd : rf) + (lane & 15);
#pragma unroll
                            for (int nn = 0; nn < 8; nn++) {
                                uint32_t vf[4];
                                ldm4t(vf, vbase + (nn >> 2) * 16384 + R * 128 + (((((nn & 3) * 2) + (lane >> 4)) ^ (lane & 7)) << 4));
                                mma16(o + 8 * nn, pa[1 + 2 * pass][0], pa[1 + 2 * pass][1], pa[2 + 2 * pass][0], pa[2 + 2 * pass][1], vf[0], vf[1]);
                                mma16(o + 8 * nn + 4, pa[1 + 2 * pass][0], pa[1 + 2 * pass][1], pa[2 + 2 * pass][0], pa[2 + 2 * pass][1], vf[2], vf[3]);
                            }
                        }
                    }
                }
                __syncwarp();
                if (lane < 2) mbar_arrive_cl(empty_a + st * 8);
                if (++st == NSTAGE) { st = 0; ph ^= 1; }
#pragma unroll
                for (int b = 0; b < 2; b++)
                    store_box([&](int i) { const float sc = (i & 2) ? l1 : l0; return pk(o[32 * b + i] * sc, o[32 * b + i + 1] * sc); },
                              stg + (b & 1) * 2048, soff, &P.m[M_SO], nt * 256 + hh * 128 + b * 64, row0, lane);
            }
            pend = &g_sync.oc[blk][nt];
        } else if (type == T_A) {
#pragma unroll
            for (int b = 0; b < 4; b++)
                store_box([&](int i) { return pk(acc[32 * b + i], acc[32 * b + i + 1]); }, stg + (b & 1) * 2048, soff, &P.m[M_SKV],
                          nt * 256 + b * 64, row0, lane);
            pend = &g_sync.kv[blk][nt];
        } else if (type == T_C) {
#pragma unroll
            for (int b = 0; b < 2; b++)
                store_box([&](int i) { return pk(acc[32 * b + i] * acc[64 + 32 * b + i], acc[32 * b + i + 1] * acc[64 + 32 * b + i + 1]); },
                          stg + (b & 1) * 2048, soff, &P.m[M_SH], nt * 128 + b * 64, row0, lane);
            pend = &g_sync.hc[blk];
        } else if (type == T_E) {
            const size_t o0 = (size_t)(row0 + g) * DM + nt * 256 + 2 * t;
            const uint32_t* xp = (const uint32_t*)(P.x + o0);
            float* ap = g_acc + o0;
#pragma unroll
            for (int i = 0; i < 32; i++) {
                uint32_t x0 = __ldg(xp + i * 4), x1 = __ldg(xp + i * 4 + 8 * DM / 2);
                *(float2*)(ap + i * 8) = make_float2(acc[4 * i] + __uint_as_float(x0 << 16), acc[4 * i + 1] + __uint_as_float(x0 & 0xffff0000u));
                *(float2*)(ap + i * 8 + 8 * DM) = make_float2(acc[4 * i + 2] + __uint_as_float(x1 << 16), acc[4 * i + 3] + __uint_as_float(x1 & 0xffff0000u));
            }
            __syncwarp();
            if (lane == 0) { fence_gpu(); red_add(&g_sync.acc[blk][nt], 1); }
        } else if (type == T_D) {
            const int nsplit = ty;
            if (lane == 0) wait_cnt(&g_sync.acc[blk][nt], (E + 1) * 8);
            __syncwarp();
            float* ap = g_acc + (size_t)(row0 + g) * DM + nt * 256 + 2 * t;
            bool fin = true;
            if (nsplit) {
#pragma unroll
                for (int i = 0; i < 32; i++) {
                    asm volatile("red.relaxed.gpu.global.add.v2.f32 [%0], {%1,%2};" ::"l"(ap + i * 8), "f"(acc[4 * i]), "f"(acc[4 * i + 1]) : "memory");
                    asm volatile("red.relaxed.gpu.global.add.v2.f32 [%0], {%1,%2};" ::"l"(ap + i * 8 + 8 * DM), "f"(acc[4 * i + 2]), "f"(acc[4 * i + 3]) : "memory");
                }
                fence_gpu();
                __syncwarp();
                unsigned old = 0;
                if (lane == 0) { old = atomicAdd(&g_sync.dc[blk][nt][cw], 1); fence_gpu(); }
                old = __shfl_sync(~0u, old, 0);
                fin = (old + 1 == (E + 1) * (unsigned)nsplit);
#pragma unroll
                for (int i = 0; i < 128; i++) acc[i] = 0.f;
            }
            if (fin) {
#pragma unroll
                for (int i = 0; i < 32; i++) {
                    float2 a0 = ld_rlx_f2(ap + i * 8), a1 = ld_rlx_f2(ap + i * 8 + 8 * DM);
                    acc[4 * i] += a0.x; acc[4 * i + 1] += a0.y; acc[4 * i + 2] += a1.x; acc[4 * i + 3] += a1.y;
                }
#pragma unroll
                for (int b = 0; b < 4; b++)
                    store_box([&](int i) { return pk(acc[32 * b + i], acc[32 * b + i + 1]); }, stg + (b & 1) * 2048, soff, &P.m[M_SOUT],
                              nt * 256 + b * 64, row0, lane);
            }
        }
        if (urgent) flush_flag(pend, lane);
    }
    flush_flag(pend, lane);
    if (lane == 0) bulk_wait_all();
    __syncwarp();
}

__global__ void __cluster_dims__(2, 1, 1) __launch_bounds__(NTHREADS, 1) fused_kernel(const __grid_constant__ Params P) {
    extern __shared__ __align__(1024) unsigned char smem[];
    const uint32_t sb = smem_u32(smem);
    const int tid = threadIdx.x, lane = tid & 31, warp = __shfl_sync(~0u, tid >> 5, 0);
    uint32_t rank;
    asm volatile("mov.u32 %0, %%cluster_ctarank;" : "=r"(rank));
    if (tid == 0) {
        if (sb & 1023) __trap();
        for (int i = 0; i < NSTAGE; i++) { mbar_init(sb + B_FULL + i * 8, 1); mbar_init(sb + B_EMPTY + i * 8, 16); }
        for (int i = 0; i < 2; i++) { mbar_init(sb + B_TFULL + i * 8, 1); mbar_init(sb + B_TEMPTY + i * 8, 17); }
        mbar_init(sb + B_ROLE, 1);
        mbar_init(sb + B_WQ, 1); mbar_init(sb + B_WK, 1); mbar_init(sb + B_WV, 1); mbar_init(sb + B_WO, 1);
        for (int i = 0; i < 4; i++) mbar_init(sb + B_KV + i * 8, 1);
        mbar_init(sb + B_S, 1);
        asm volatile("fence.mbarrier_init.release.cluster;" ::: "memory");
    }
    __syncthreads();
    cluster_arrive();
    if (warp < 4) {
        asm volatile("setmaxnreg.dec.sync.aligned.u32 40;");
        if (rank == 0 && lane == 0) {
            if (warp < 2) {
                unsigned best = 1u << 30;
                unsigned* p = g_probe + warp * 1024 + (blockIdx.x >> 1 & 31) * 32;
#pragma unroll 1
                for (int r = 0; r < 4; r++) {
                    unsigned t0, t1, v;
                    asm volatile("mov.u32 %0, %%clock;" : "=r"(t0)::"memory");
                    asm volatile("atom.relaxed.gpu.global.add.u32 %0, [%1], 0;" : "=r"(v) : "l"(p) : "memory");
                    asm volatile("{ .reg .u32 z; and.b32 z, %1, 0; mov.u32 %0, %%clock; add.u32 %0, %0, z; }" : "=r"(t1) : "r"(v) : "memory");
                    best = min(best, t1 - t0);
                }
                sts1(sb + S_PROBE + warp * 4, best);
            } else if (warp == 2) {
                sts1(sb + S_PROBE + 8, atomicAdd(&g_sync.start, 1) / NPAIR);
            }
        }
        if (warp == 3 && lane < 4) {
            if (blockIdx.x < 128) l2_prefetch((const char*)P.w[lane] + (size_t)blockIdx.x * 32768, 32768);
        }
        bar_sync(7, 128);
        cluster_wait();
        if (rank == 0 && tid == 0) {
            const unsigned E = lds1(sb + S_PROBE + 8);
            const int side = lds1(sb + S_PROBE + 4) < lds1(sb + S_PROBE);
            if (blockIdx.x == 0) { g_sync.tick[(E + 2) & 3][0] = 0; g_sync.tick[(E + 2) & 3][1] = 0; g_sync.task[(E + 2) & 3] = 0; }
            unsigned tk = atomicAdd(&g_sync.tick[E & 3][side], 1);
            int role = -1;
            if (side == 1) { if (tk < 32) role = tk; }
            else if (tk < 32) {
                long long t0 = clock64();
                unsigned n0, n1;
                while (true) {
                    n1 = ld_rlx(&g_sync.tick[E & 3][1]); n0 = ld_rlx(&g_sync.tick[E & 3][0]);
                    if (n1 >= 32 || n0 + n1 >= NPAIR) break;
                    if (clock64() - t0 > TIMEOUT) __trap();
                }
                if (n1 < 32 && tk < 32 - n1) role = n1 + tk;
            }
            bcast2(sb + S_ROLE, sb + B_ROLE, (uint32_t)role, E);
        }
        __syncwarp();
        mbar_wait_cl(sb + B_ROLE, 0);
        const int role = (int)lds1(sb + S_ROLE);
        const unsigned E = lds1(sb + S_ROLE + 4);
        if (role >= 0) {
            chain_helper(P, sb, role, rank, E, warp, lane);
            fence_async_all();
            cluster_arrive(); cluster_wait();
        }
        if (tid == 0) bulk_producer(P, sb, rank, E);
        __syncwarp();
        cluster_arrive(); cluster_wait();
    } else {
        asm volatile("setmaxnreg.inc.sync.aligned.u32 232;");
        const int cw = warp - 4;
        if (blockIdx.x < 128) {
            const int row = blockIdx.x * 16 + cw * 2;
            uint4 v[2][2];
#pragma unroll
            for (int r = 0; r < 2; r++) {
                const uint4* p = (const uint4*)(P.x + (size_t)(row + r) * DM);
                v[r][0] = __ldg(p + lane); v[r][1] = __ldg(p + 32 + lane);
            }
#pragma unroll
            for (int r = 0; r < 2; r++) {
                float f[16];
                const uint32_t w[8] = {v[r][0].x, v[r][0].y, v[r][0].z, v[r][0].w, v[r][1].x, v[r][1].y, v[r][1].z, v[r][1].w};
                float s = 0.f;
#pragma unroll
                for (int i = 0; i < 8; i++) { f[2 * i] = __uint_as_float(w[i] << 16); f[2 * i + 1] = __uint_as_float(w[i] & 0xffff0000u); s += f[2 * i] + f[2 * i + 1]; }
#pragma unroll
                for (int o = 16; o; o >>= 1) s += __shfl_xor_sync(~0u, s, o);
                const float mean = s * (1.f / DM);
                float q = 0.f;
#pragma unroll
                for (int i = 0; i < 16; i++) { f[i] -= mean; q += f[i] * f[i]; }
#pragma unroll
                for (int o = 16; o; o >>= 1) q += __shfl_xor_sync(~0u, q, o);
                const float rs = rsqrtf(q * (1.f / DM) + 1e-5f);
                uint4* d = (uint4*)(g_xn + (size_t)(row + r) * DM);
                d[lane] = make_uint4(pk(f[0] * rs, f[1] * rs), pk(f[2] * rs, f[3] * rs), pk(f[4] * rs, f[5] * rs), pk(f[6] * rs, f[7] * rs));
                d[32 + lane] = make_uint4(pk(f[8] * rs, f[9] * rs), pk(f[10] * rs, f[11] * rs), pk(f[12] * rs, f[13] * rs), pk(f[14] * rs, f[15] * rs));
            }
            fence_async_all();
            __syncwarp();
            if (lane == 0) { fence_gpu(); red_add(&g_sync.ln[row >> 7], 1); }
        }
        cluster_wait();
        mbar_wait_cl(sb + B_ROLE, 0);
        const int role = (int)lds1(sb + S_ROLE);
        const unsigned E = lds1(sb + S_ROLE + 4);
        int phase = role >= 0 ? 0 : 1;
#pragma unroll 1
        while (true) {
            if (phase == 0) {
                chain_compute(P, sb, role, rank, E, cw, lane);
                fence_async_all();
                cluster_arrive(); cluster_wait();
            } else if (phase == 1) {
                bulk_consumer(P, sb, rank, E, cw, lane);
            } else break;
            asm volatile("add.s32 %0, %0, 1;" : "+r"(phase));
        }
        cluster_arrive(); cluster_wait();
    }
}

typedef CUresult (*EncodeFn)(CUtensorMap*, CUtensorMapDataType, cuuint32_t, void*, const cuuint64_t*, const cuuint64_t*, const cuuint32_t*,
                             const cuuint32_t*, CUtensorMapInterleave, CUtensorMapSwizzle, CUtensorMapL2promotion, CUtensorMapFloatOOBfill);

static void map2d(EncodeFn fn, CUtensorMap* m, const void* base, uint64_t cols, uint64_t rows, uint32_t bc, uint32_t br) {
    cuuint64_t dims[2] = {cols, rows};
    cuuint64_t strides[1] = {cols * 2};
    cuuint32_t box[2] = {bc, br}, es[2] = {1, 1};
    fn(m, CU_TENSOR_MAP_DATA_TYPE_BFLOAT16, 2, (void*)base, dims, strides, box, es, CU_TENSOR_MAP_INTERLEAVE_NONE, CU_TENSOR_MAP_SWIZZLE_128B,
       CU_TENSOR_MAP_L2_PROMOTION_L2_256B, CU_TENSOR_MAP_FLOAT_OOB_FILL_NONE);
}
static void map4d(EncodeFn fn, CUtensorMap* m, const void* base) {
    cuuint64_t dims[4] = {4096, 4, 8, 16};
    cuuint64_t strides[3] = {8 * 8192, 8192, 32 * 8192};
    cuuint32_t box[4] = {64, 4, 8, 8}, es[4] = {1, 1, 1, 1};
    fn(m, CU_TENSOR_MAP_DATA_TYPE_BFLOAT16, 4, (void*)base, dims, strides, box, es, CU_TENSOR_MAP_INTERLEAVE_NONE, CU_TENSOR_MAP_SWIZZLE_128B,
       CU_TENSOR_MAP_L2_PROMOTION_L2_128B, CU_TENSOR_MAP_FLOAT_OOB_FILL_NONE);
}

extern "C" void kernel_launch(void* const* d_in, const int* in_sizes, int n_in, void* d_out, int out_size) {
    static Params P;
    static const void* key[12];
    static bool ready = false;
    bool same = ready && key[11] == d_out;
    for (int i = 0; i < 11 && same; i++) same = key[i] == d_in[i];
    if (!same) {
        void* fp = nullptr;
        cudaDriverEntryPointQueryResult qr;
        cudaGetDriverEntryPoint("cuTensorMapEncodeTiled", &fp, cudaEnableDefault, &qr);
        EncodeFn fn = (EncodeFn)fp;
        void *xn, *kv, *o, *h;
        cudaGetSymbolAddress(&xn, g_xn); cudaGetSymbolAddress(&kv, g_kv); cudaGetSymbolAddress(&o, g_o); cudaGetSymbolAddress(&h, g_h);
        map2d(fn, &P.m[M_XN], xn, DM, SEQ, 64, 64);
        map2d(fn, &P.m[M_H], h, FF, SEQ, 64, 64);
        map2d(fn, &P.m[M_O], o, 4096, SEQ, 64, 64);
        map2d(fn, &P.m[M_KVL], kv, 8192, SEQ, 64, 64);
        map2d(fn, &P.m[M_WQ], d_in[2], 4096, DM, 64, 64);
        map2d(fn, &P.m[M_WK], d_in[3], 4096, DM, 64, 64);
        map2d(fn, &P.m[M_WV], d_in[4], 4096, DM, 64, 64);
        map2d(fn, &P.m[M_WG], d_in[8], FF, DM, 64, 64);
        map2d(fn, &P.m[M_WU], d_in[9], FF, DM, 64, 64);
        map2d(fn, &P.m[M_WD], d_in[10], DM, FF, 64, 64);
        map2d(fn, &P.m[M_WO], d_in[5], DM, 4096, 64, 64);
        map2d(fn, &P.m[M_KVC], kv, 8192, SEQ, 64, 32);
        map2d(fn, &P.m[M_SKV], kv, 8192, SEQ, 64, 16);
        map2d(fn, &P.m[M_SO], o, 4096, SEQ, 64, 16);
        map2d(fn, &P.m[M_SH], h, FF, SEQ, 64, 16);
        map2d(fn, &P.m[M_SOUT], d_out, DM, SEQ, 64, 16);
        map4d(fn, &P.m[M_CQ], d_in[2]);
        map4d(fn, &P.m[M_CK], d_in[3]);
        map4d(fn, &P.m[M_CV], d_in[4]);
        P.x = (const __nv_bfloat16*)d_in[0];
        P.mem0 = (const __nv_bfloat16*)d_in[1];
        P.w[0] = (const __nv_bfloat16*)d_in[3]; P.w[1] = (const __nv_bfloat16*)d_in[4];
        P.w[2] = (const __nv_bfloat16*)d_in[2]; P.w[3] = (const __nv_bfloat16*)d_in[5];
        P.out = (__nv_bfloat16*)d_out;
        cudaFuncSetAttribute(fused_kernel, cudaFuncAttributeMaxDynamicSharedMemorySize, SMEM_BYTES);
        for (int i = 0; i < 11; i++) key[i] = d_in[i];
        key[11] = d_out;
        ready = true;
    }
    fused_kernel<<<NCTA, NTHREADS, SMEM_BYTES, cudaStreamPerThread>>>(P);
}
```

```cpp
#include <cuda_runtime.h>
#include <cuda_bf16.h>
#include <cuda.h>
#include <stdint.h>

#define DEV __device__ __forceinline__
#define TRAPV(v) __trap()

constexpr int SEQ = 2048, DM = 512, NH = 32, DH = 128, FF = 1376, NSEG = 64;
constexpr int NCTA = 132, NPAIR = 66, NTHREADS = 384;

__device__ __align__(1024) __nv_bfloat16 g_xn[SEQ * DM];
__device__ __align__(1024) __nv_bfloat16 g_kv[SEQ * 8192];
__device__ __align__(1024) __nv_bfloat16 g_o[SEQ * 4096];
__device__ __align__(1024) __nv_bfloat16 g_h[SEQ * FF];
__device__ __align__(1024) float g_acc[SEQ * DM];
__device__ __align__(1024) uint4 g_kvm[NSEG * NH * 2 * 4 * 32];
__device__ __align__(1024) uint4 g_arena[(4 << 20) / 16];

struct Sync {
    unsigned start;        unsigned tick[4][2];   unsigned p1[23];
    unsigned task[4];      unsigned p2[28];
    unsigned chain_ready;  unsigned p3[31];
    unsigned ln[16];       unsigned ai[16];
    unsigned hc[16];       unsigned p5[16];
    unsigned kv[16][32];
    unsigned oc[18][16];
    unsigned dc[16][2][8];
    unsigned prog[64][8];
};
__device__ __align__(1024) Sync g_sync;

enum { M_XN = 0, M_H, M_O, M_KVL, M_WQ, M_WK, M_WV, M_WG, M_WU, M_WD, M_WO, M_KVC, M_SKV, M_SO, M_SH, M_RACC, M_COUNT };
struct __align__(64) Params {
    CUtensorMap m[M_COUNT];
    const __nv_bfloat16* x;
    const __nv_bfloat16* mem0;
    const __nv_bfloat16* w[4];
    __nv_bfloat16* out;
    char* arena;
    const char* pg[64];
    uint32_t zs[96];
};

enum { T_A = 0, T_B = 1, T_C = 2, T_E = 3, T_D = 4, T_END = 7 };
#define NTASK 604
__device__ const __align__(128) uint2 g_tasks[NTASK] = {
    {0x18800000u,0u}, {0x18800100u,0u}, {0x18800200u,0u}, {0x18800300u,0u}, {0x18800400u,0u}, {0x18800500u,0u}, {0x18800600u,0u}, {0x18800700u,0u},
    {0x18800800u,0u}, {0x18800900u,0u}, {0x18800a00u,0u}, {0x18800b00u,0u}, {0x18800c00u,0u}, {0x18800d00u,0u}, {0x18800e00u,0u}, {0x18800f00u,0u},
    {0x18801000u,0u}, {0x18801100u,0u}, {0x18801200u,0u}, {0x18801300u,0u}, {0x18801400u,0u}, {0x18801500u,0u}, {0x18801600u,0u}, {0x18801700u,0u},
    {0x18801800u,0u}, {0x18801900u,0u}, {0x18801a00u,0u}, {0x18801b00u,0u}, {0x18801c00u,0u}, {0x18801d00u,0u}, {0x18801e00u,0u}, {0x18801f00u,0u},
    {0x18800010u,0u}, {0x18800110u,0u}, {0x18800210u,0u}, {0x18800310u,0u}, {0x18800410u,0u}, {0x18800510u,0u}, {0x18800610u,0u}, {0x18800710u,0u},
    {0x18800810u,0u}, {0x18800910u,0u}, {0x18800a10u,0u}, {0x18800b10u,0u}, {0x18800c10u,0u}, {0x18800d10u,0u}, {0x18800e10u,0u}, {0x18800f10u,0u},
    {0x18801010u,0u}, {0x18801110u,0u}, {0x18801210u,0u}, {0x18801310u,0u}, {0x18801410u,0u}, {0x18801510u,0u}, {0x18801610u,0u}, {0x18801710u,0u},
    {0x18801810u,0u}, {0x18801910u,0u}, {0x18801a10u,0u}, {0x18801b10u,0u}, {0x18801c10u,0u}, {0x18801d10u,0u}, {0x18801e10u,0u}, {0x18801f10u,0u},
    {0x00800020u,0u}, {0x00800120u,0u}, {0x00800220u,0u}, {0x00800320u,0u}, {0x00800420u,0u}, {0x00800520u,0u}, {0x00800620u,0u}, {0x00800720u,0u},
    {0x00800820u,0u}, {0x00800920u,0u}, {0x00800a20u,0u}, {0x00800b20u,0u}, {0x00800c20u,0u}, {0x00800d20u,0u}, {0x00800e20u,0u}, {0x00800f20u,0u},
    {0x00801020u,0u}, {0x00801120u,0u}, {0x00801220u,0u}, {0x00801320u,0u}, {0x00801420u,0u}, {0x00801520u,0u}, {0x00801620u,0u}, {0x00801720u,0u},
    {0x00801820u,0u}, {0x00801920u,0u}, {0x00801a20u,0u}, {0x00801b20u,0u}, {0x00801c20u,0u}, {0x00801d20u,0u}, {0x00801e20u,0u}, {0x00801f20u,0u},
    {0x00800040u,0u}, {0x00800140u,0u}, {0x00800240u,0u}, {0x00800340u,0u}, {0x00800440u,0u}, {0x00800540u,0u}, {0x00800640u,0u}, {0x00800740u,0u},
    {0x00800840u,0u}, {0x00800940u,0u}, {0x00800a40u,0u}, {0x00800b40u,0u}, {0x00800c40u,0u}, {0x00800d40u,0u}, {0x00800e40u,0u}, {0x00800f40u,0u},
    {0x00801040u,0u}, {0x00801140u,0u}, {0x00801240u,0u}, {0x00801340u,0u}, {0x00801440u,0u}, {0x00801540u,0u}, {0x00801640u,0u}, {0x00801740u,0u},
    {0x00801840u,0u}, {0x00801940u,0u}, {0x00801a40u,0u}, {0x00801b40u,0u}, {0x00801c40u,0u}, {0x00801d40u,0u}, {0x00801e40u,0u}, {0x00801f40u,0u},
    {0x00800060u,0u}, {0x00800160u,0u}, {0x00800260u,0u}, {0x00800360u,0u}, {0x00800460u,0u}, {0x00800560u,0u}, {0x00800660u,0u}, {0x00800760u,0u},
    {0x08800001u,0u}, {0x08800101u,0u}, {0x08800201u,0u}, {0x08800301u,0u}, {0x08800401u,0u}, {0x08800501u,0u}, {0x08800601u,0u}, {0x08800701u,0u},
    {0x08800801u,0u}, {0x08800901u,0u}, {0x08800a01u,0u}, {0x08800b01u,0u}, {0x08800c01u,0u}, {0x08800d01u,0u}, {0x08800e01u,0u}, {0x08800f01u,0u},
    {0x00800860u,0u}, {0x00800960u,0u}, {0x00800a60u,0u}, {0x00800b60u,0u}, {0x00800c60u,0u}, {0x00800d60u,0u}, {0x00800e60u,0u}, {0x00800f60u,0u},
    {0x00801060u,0u}, {0x00801160u,0u}, {0x00801260u,0u}, {0x00801360u,0u}, {0x00801460u,0u}, {0x00801560u,0u}, {0x00801660u,0u}, {0x00801760u,0u},
    {0x00801860u,0u}, {0x00801960u,0u}, {0x00801a60u,0u}, {0x00801b60u,0u}, {0x00801c60u,0u}, {0x00801d60u,0u}, {0x00801e60u,0u}, {0x00801f60u,0u},
    {0x00800080u,0u}, {0x00800180u,0u}, {0x00800280u,0u}, {0x00800380u,0u}, {0x00800480u,0u}, {0x00800580u,0u}, {0x00800680u,0u}, {0x00800780u,0u},
    {0x00800880u,0u}, {0x00800980u,0u}, {0x00800a80u,0u}, {0x00800b80u,0u}, {0x02000004u,771u}, {0x02000104u,771u}, {0x02040004u,771u}, {0x02040104u,771u},
    {0x00800c80u,0u}, {0x00800d80u,0u}, {0x00800e80u,0u}, {0x00800f80u,0u}, {0x00801080u,0u}, {0x00801180u,0u}, {0x00801280u,0u}, {0x00801380u,0u},
    {0x00801480u,0u}, {0x00801580u,0u}, {0x00801680u,0u}, {0x00801780u,0u}, {0x00801880u,0u}, {0x00801980u,0u}, {0x00801a80u,0u}, {0x00801b80u,0u},
    {0x00801c80u,0u}, {0x00801d80u,0u}, {0x00801e80u,0u}, {0x00801f80u,0u}, {0x008000a0u,0u}, {0x008001a0u,0u}, {0x008002a0u,0u}, {0x008003a0u,0u},
    {0x008004a0u,0u}, {0x008005a0u,0u}, {0x008006a0u,0u}, {0x008007a0u,0u}, {0x008008a0u,0u}, {0x008009a0u,0u}, {0x00800aa0u,0u}, {0x00800ba0u,0u},
    {0x00800ca0u,0u}, {0x00800da0u,0u}, {0x00800ea0u,0u}, {0x00800fa0u,0u}, {0x008010a0u,0u}, {0x008011a0u,0u}, {0x008012a0u,0u}, {0x008013a0u,0u},
    {0x008014a0u,0u}, {0x008015a0u,0u}, {0x008016a0u,0u}, {0x008017a0u,0u}, {0x008018a0u,0u}, {0x008019a0u,0u}, {0x00801aa0u,0u}, {0x00801ba0u,0u},
    {0x00801ca0u,0u}, {0x00801da0u,0u}, {0x00801ea0u,0u}, {0x00801fa0u,0u}, {0x008000c0u,0u}, {0x008001c0u,0u}, {0x008002c0u,0u}, {0x008003c0u,0u},
    {0x08800021u,0u}, {0x08800121u,0u}, {0x08800221u,0u}, {0x08800321u,0u}, {0x08800421u,0u}, {0x08800521u,0u}, {0x08800621u,0u}, {0x08800721u,0u},
    {0x08800821u,0u}, {0x08800921u,0u}, {0x08800a21u,0u}, {0x08800b21u,0u}, {0x08800c21u,0u}, {0x08800d21u,0u}, {0x08800e21u,0u}, {0x08800f21u,0u},
    {0x008004c0u,0u}, {0x008005c0u,0u}, {0x008006c0u,0u}, {0x008007c0u,0u}, {0x008008c0u,0u}, {0x008009c0u,0u}, {0x00800ac0u,0u}, {0x00800bc0u,0u},
    {0x00800cc0u,0u}, {0x00800dc0u,0u}, {0x00800ec0u,0u}, {0x00800fc0u,0u}, {0x008010c0u,0u}, {0x008011c0u,0u}, {0x02000024u,771u}, {0x02000124u,771u},
    {0x008012c0u,0u}, {0x008013c0u,0u}, {0x008014c0u,0u}, {0x008015c0u,0u}, {0x008016c0u,0u}, {0x008017c0u,0u}, {0x008018c0u,0u}, {0x008019c0u,0u},
    {0x00801ac0u,0u}, {0x00801bc0u,0u}, {0x00801cc0u,0u}, {0x00801dc0u,0u}, {0x00801ec0u,0u}, {0x00801fc0u,0u}, {0x008000e0u,0u}, {0x008001e0u,0u},
    {0x02040024u,771u}, {0x02040124u,771u}, {0x008002e0u,0u}, {0x008003e0u,0u}, {0x008004e0u,0u}, {0x008005e0u,0u}, {0x008006e0u,0u}, {0x008007e0u,0u},
    {0x008008e0u,0u}, {0x008009e0u,0u}, {0x00800ae0u,0u}, {0x00800be0u,0u}, {0x00800ce0u,0u}, {0x00800de0u,0u}, {0x00800ee0u,0u}, {0x00800fe0u,0u},
    {0x008010e0u,0u}, {0x008011e0u,0u}, {0x008012e0u,0u}, {0x008013e0u,0u}, {0x008014e0u,0u}, {0x008015e0u,0u}, {0x008016e0u,0u}, {0x008017e0u,0u},
    {0x008018e0u,0u}, {0x008019e0u,0u}, {0x00801ae0u,0u}, {0x00801be0u,0u}, {0x00801ce0u,0u}, {0x00801de0u,0u}, {0x00801ee0u,0u}, {0x00801fe0u,0u},
    {0x08800041u,0u}, {0x08800141u,0u}, {0x08800241u,0u}, {0x08800341u,0u}, {0x08800441u,0u}, {0x08800541u,0u}, {0x08800641u,0u}, {0x08800741u,0u},
    {0x08800841u,0u}, {0x08800941u,0u}, {0x08800a41u,0u}, {0x08800b41u,0u}, {0x08800c41u,0u}, {0x08800d41u,0u}, {0x08800e41u,0u}, {0x08800f41u,0u},
    {0x00800002u,0u}, {0x00800102u,0u}, {0x00800202u,0u}, {0x00800302u,0u}, {0x00800402u,0u}, {0x00800502u,0u}, {0x00800602u,0u}, {0x00800702u,0u},
    {0x00800802u,0u}, {0x00800902u,0u}, {0x00800a02u,0u}, {0x00800022u,0u}, {0x00800122u,0u}, {0x00800222u,0u}, {0x02000044u,771u}, {0x02000144u,771u},
    {0x02040044u,771u}, {0x02040144u,771u}, {0x01600003u,771u}, {0x01600103u,771u}, {0x00800322u,0u}, {0x00800422u,0u}, {0x00800522u,0u}, {0x00800622u,0u},
    {0x00800722u,0u}, {0x00800822u,0u}, {0x00800922u,0u}, {0x00800a22u,0u}, {0x00800042u,0u}, {0x00800142u,0u}, {0x00800242u,0u}, {0x00800342u,0u},
    {0x00800442u,0u}, {0x00800542u,0u}, {0x00800642u,0u}, {0x00800742u,0u}, {0x00800842u,0u}, {0x00800942u,0u}, {0x00800a42u,0u}, {0x00800062u,0u},
    {0x00800162u,0u}, {0x00800262u,0u}, {0x00800362u,0u}, {0x00800462u,0u}, {0x00800562u,0u}, {0x00800662u,0u}, {0x01600023u,771u}, {0x01600123u,771u},
    {0x01600043u,771u}, {0x01600143u,771u}, {0x00800762u,0u}, {0x00800862u,0u}, {0x00800962u,0u}, {0x00800a62u,0u}, {0x00800082u,0u}, {0x00800182u,0u},
    {0x00800282u,0u}, {0x00800382u,0u}, {0x00800482u,0u}, {0x00800582u,0u}, {0x00800682u,0u}, {0x00800782u,0u}, {0x00800882u,0u}, {0x00800982u,0u},
    {0x00800a82u,0u}, {0x008000a2u,0u}, {0x008001a2u,0u}, {0x008002a2u,0u}, {0x008003a2u,0u}, {0x008004a2u,0u}, {0x08800061u,0u}, {0x08800161u,0u},
    {0x08800261u,0u}, {0x08800361u,0u}, {0x08800461u,0u}, {0x08800561u,0u}, {0x08800661u,0u}, {0x08800761u,0u}, {0x08800861u,0u}, {0x08800961u,0u},
    {0x08800a61u,0u}, {0x08800b61u,0u}, {0x08800c61u,0u}, {0x08800d61u,0u}, {0x08800e61u,0u}, {0x08800f61u,0u}, {0x01600063u,771u}, {0x01600163u,771u},
    {0x01600083u,771u}, {0x01600183u,771u}, {0x008005a2u,0u}, {0x008006a2u,0u}, {0x008007a2u,0u}, {0x008008a2u,0u}, {0x008009a2u,0u}, {0x00800aa2u,0u},
    {0x008000c2u,0u}, {0x008001c2u,0u}, {0x008002c2u,0u}, {0x008003c2u,0u}, {0x02000064u,771u}, {0x02000164u,771u}, {0x008004c2u,0u}, {0x008005c2u,0u},
    {0x02040064u,771u}, {0x02040164u,771u}, {0x008006c2u,0u}, {0x008007c2u,0u}, {0x008008c2u,0u}, {0x008009c2u,0u}, {0x00800ac2u,0u}, {0x008000e2u,0u},
    {0x008001e2u,0u}, {0x008002e2u,0u}, {0x008003e2u,0u}, {0x008004e2u,0u}, {0x016000a3u,1285u}, {0x016001a3u,1285u}, {0x008005e2u,0u}, {0x008006e2u,0u},
    {0x008007e2u,0u}, {0x008008e2u,0u}, {0x008009e2u,0u}, {0x00800ae2u,0u}, {0x016000c3u,1285u}, {0x016001c3u,1285u}, {0x016000ebu,2313u}, {0x016000fbu,4361u},
    {0x08800081u,0u}, {0x08800181u,0u}, {0x08800281u,0u}, {0x08800381u,0u}, {0x08800481u,0u}, {0x08800581u,0u}, {0x08800681u,0u}, {0x08800781u,0u},
    {0x08800881u,0u}, {0x08800981u,0u}, {0x08800a81u,0u}, {0x08800b81u,0u}, {0x08800c81u,0u}, {0x08800d81u,0u}, {0x08800e81u,0u}, {0x08800f81u,0u},
    {0x02000084u,771u}, {0x02000184u,771u}, {0x02040084u,771u}, {0x02040184u,771u}, {0x088000a1u,0u}, {0x088001a1u,0u}, {0x088002a1u,0u}, {0x088003a1u,0u},
    {0x088004a1u,0u}, {0x088005a1u,0u}, {0x088006a1u,0u}, {0x088007a1u,0u}, {0x088008a1u,0u}, {0x088009a1u,0u}, {0x08800aa1u,0u}, {0x08800ba1u,0u},
    {0x08800ca1u,0u}, {0x08800da1u,0u}, {0x08800ea1u,0u}, {0x08800fa1u,0u}, {0x010000a4u,1285u}, {0x010001a4u,1285u}, {0x010200a4u,1285u}, {0x010201a4u,1285u},
    {0x010400a4u,1285u}, {0x010401a4u,1285u}, {0x010600a4u,1285u}, {0x010601a4u,1285u}, {0x088000c1u,0u}, {0x088001c1u,0u}, {0x088002c1u,0u}, {0x088003c1u,0u},
    {0x088004c1u,0u}, {0x088005c1u,0u}, {0x088006c1u,0u}, {0x088007c1u,0u}, {0x088008c1u,0u}, {0x088009c1u,0u}, {0x08800ac1u,0u}, {0x08800bc1u,0u},
    {0x08800cc1u,0u}, {0x08800dc1u,0u}, {0x08800ec1u,0u}, {0x08800fc1u,0u}, {0x088000e9u,0u}, {0x088002e9u,0u}, {0x088004e9u,0u}, {0x088006e9u,0u},
    {0x088008e9u,0u}, {0x08800ae9u,0u}, {0x08800ce9u,0u}, {0x08800ee9u,0u}, {0x010000c4u,1285u}, {0x010001c4u,1285u}, {0x010200c4u,1285u}, {0x010201c4u,1285u},
    {0x010400c4u,1285u}, {0x010401c4u,1285u}, {0x010600c4u,1285u}, {0x010601c4u,1285u}, {0x088000f9u,0u}, {0x088002f9u,0u}, {0x088004f9u,0u}, {0x088006f9u,0u},
    {0x088008f9u,0u}, {0x08800af9u,0u}, {0x08800cf9u,0u}, {0x08800ef9u,0u}, {0x008000ecu,2313u}, {0x008100ecu,2313u}, {0x008200ecu,2313u}, {0x008300ecu,2313u},
    {0x008400ecu,2313u}, {0x008500ecu,2313u}, {0x008600ecu,2313u}, {0x008700ecu,2313u}, {0x108000fcu,4361u}, {0x108100fcu,4361u}, {0x108200fcu,4361u}, {0x108300fcu,4361u},
    {0x108400fcu,4361u}, {0x108500fcu,4361u}, {0x108600fcu,4361u}, {0x108700fcu,4361u}, {0x304000fcu,4361u}, {0x304080fcu,4361u}, {0x304100fcu,4361u}, {0x304180fcu,4361u},
    {0x304200fcu,4361u}, {0x304280fcu,4361u}, {0x304300fcu,4361u}, {0x304380fcu,4361u}, {0x304400fcu,4361u}, {0x304480fcu,4361u}, {0x304500fcu,4361u}, {0x304580fcu,4361u},
    {0x304600fcu,4361u}, {0x304680fcu,4361u}, {0x304700fcu,4361u}, {0x304780fcu,4361u}, {0x204000fcu,4361u}, {0x204080fcu,4361u}, {0x204100fcu,4361u}, {0x204180fcu,4361u},
    {0x204200fcu,4361u}, {0x204280fcu,4361u}, {0x204300fcu,4361u}, {0x204380fcu,4361u}, {0x204400fcu,4361u}, {0x204480fcu,4361u}, {0x204500fcu,4361u}, {0x204580fcu,4361u},
    {0x204600fcu,4361u}, {0x204680fcu,4361u}, {0x204700fcu,4361u}, {0x204780fcu,4361u},
};

constexpr int STAGE_BYTES = 49152, NSTAGE = 4;
constexpr int SM_STAGING = NSTAGE * STAGE_BYTES;
constexpr int SM_BAR = SM_STAGING + 32768;
constexpr int SMEM_BYTES = SM_BAR + 3072;
constexpr int B_FULL = SM_BAR, B_EMPTY = SM_BAR + 32, B_TFULL = SM_BAR + 64, B_TEMPTY = SM_BAR + 80, B_ROLE = SM_BAR + 96,
              B_WQ = SM_BAR + 104, B_WK = SM_BAR + 112, B_WV = SM_BAR + 120, B_WO = SM_BAR + 128, B_KV = SM_BAR + 136  ,
              B_S = SM_BAR + 168, B_VL = SM_BAR + 176, B_G = SM_BAR + 184, B_VR = SM_BAR + 192, B_P = SM_BAR + 200;
constexpr int S_TASK = SM_BAR + 256  , S_ROLE = SM_BAR + 272  , S_PROBE = SM_BAR + 288  ,
              S_FLAG = SM_BAR + 352, S_CH = SM_BAR + 368  , S_PH = SM_BAR + 416  , S_DP = SM_BAR + 356, S_ONES = SM_BAR + 1024  ;
constexpr int C_FQ = 0, C_FK = 32768, C_WO = 65536;
constexpr int C_RV = 131072, C_RK = C_RV + 24576, C_VO = C_RK + 12288, C_MEM = C_VO + 16384, C_QB = C_MEM + 8192, C_KB = C_QB + 4096,
              C_SB = C_KB + 4096, C_VP = C_SB + 5120, C_VF = C_VP + 4096, C_PB = C_VF + 2048, C_T1 = C_PB + 1024, C_T2 = C_T1 + 2048,
              C_TA = C_T2 + 2048, C_END = C_TA + 4096;
static_assert(C_END <= SM_BAR && (C_QB & 1023) == 0 && (C_MEM & 1023) == 0 && C_KB >= 196608, "smem map");
DEV uint32_t g1_base(uint32_t r) {
    const uint32_t par = (r ^ (r >> 1) ^ (r >> 2) ^ (r >> 3) ^ 1) & 1;
    return (par << 12) | ((r & 1) << 13) | ((r & 6) << 15) | ((r & 8) << 16) | ((r & 48) << 10);
}
DEV uint32_t g1_slot(uint32_t s) { return ((s & 1) << 18) | ((s & 2) << 19); }
DEV uint32_t g2_base(uint32_t r) { return (5u << 18) + (0x1000u << (r >> 5)) + ((r & 31) << 7); }
DEV uint32_t g2_slot(uint32_t s) { return (s & 3) << 14; }

#define SENT 0xFFFFFFFFu

DEV uint32_t smem_u32(const void* p) { return (uint32_t)__cvta_generic_to_shared(p); }
DEV uint32_t mapa(uint32_t a, uint32_t r) { uint32_t o; asm("mapa.shared::cluster.u32 %0, %1, %2;" : "=r"(o) : "r"(a), "r"(r)); return o; }
DEV void mbar_init(uint32_t a, uint32_t c) { asm volatile("mbarrier.init.shared::cta.b64 [%0], %1;" ::"r"(a), "r"(c) : "memory"); }
DEV void mbar_expect(uint32_t a, uint32_t b) { asm volatile("mbarrier.arrive.expect_tx.shared::cta.b64 _, [%0], %1;" ::"r"(a), "r"(b) : "memory"); }
DEV void mbar_expect_elect(uint32_t a, uint32_t b) {
    asm volatile("{ .reg .pred p; elect.sync _|p, 0xffffffff; @p mbarrier.arrive.expect_tx.shared::cta.b64 _, [%0], %1; }" ::"r"(a), "r"(b) : "memory");
}
DEV void mbar_arrive_elect(uint32_t a) {
    __syncwarp();
    asm volatile("{ .reg .pred p; elect.sync _|p, 0xffffffff; @p mbarrier.arrive.shared::cta.b64 _, [%0]; }" ::"r"(a) : "memory");
}
DEV void mbar_arrive_cl(uint32_t a) { asm volatile("mbarrier.arrive.shared::cluster.b64 _, [%0];" ::"r"(a) : "memory"); }
DEV void mbar_expect_cl(uint32_t a, uint32_t b) { asm volatile("mbarrier.arrive.expect_tx.shared::cluster.b64 _, [%0], %1;" ::"r"(a), "r"(b) : "memory"); }
DEV void st_async_u2(uint32_t a, uint32_t x, uint32_t y, uint32_t bar) {
    asm volatile("st.async.weak.shared::cluster.mbarrier::complete_tx::bytes.v2.u32 [%0], {%1,%2}, [%3];" ::"r"(a), "r"(x), "r"(y), "r"(bar) : "memory");
}
DEV void bcast2(uint32_t slot, uint32_t bar, uint32_t x, uint32_t y) {
    const uint32_t rs = mapa(slot, 1), rb = mapa(bar, 1);
    mbar_expect_cl(rb, 8); st_async_u2(rs, x, y, rb);
    mbar_expect(bar, 8); st_async_u2(slot, x, y, bar);
}
DEV bool mbar_try(uint32_t a, uint32_t par) {
    uint32_t ok;
    asm volatile("{ .reg .pred p; mbarrier.try_wait.parity.shared::cta.b64 p, [%1], %2; selp.u32 %0, 1, 0, p; }" : "=r"(ok) : "r"(a), "r"(par) : "memory");
    return ok;
}
DEV bool mbar_test(uint32_t a, uint32_t par) {
    uint32_t ok;
    asm volatile("{ .reg .pred p; mbarrier.test_wait.parity.shared::cta.b64 p, [%1], %2; selp.u32 %0, 1, 0, p; }" : "=r"(ok) : "r"(a), "r"(par) : "memory");
    return ok;
}
DEV bool mbar_try_cl(uint32_t a, uint32_t par) {
    uint32_t ok;
    asm volatile("{ .reg .pred p; mbarrier.try_wait.parity.acquire.cluster.shared::cta.b64 p, [%1], %2; selp.u32 %0, 1, 0, p; }" : "=r"(ok) : "r"(a), "r"(par) : "memory");
    return ok;
}
#define HOLD 12
#define INITT 352
#define WSL 100
#define WSF 200
#define WSP 1500
constexpr long long TIMEOUT = 1000000000LL;
DEV void mbar_wait_slow(uint32_t a, uint32_t par) {
    long long t0 = clock64();
    while (!mbar_try_cl(a, par)) { if (clock64() - t0 > TIMEOUT) TRAPV((a & 0xffffff) * 2 + par); }
}
DEV void mbar_wait(uint32_t a, uint32_t par) {
    unsigned it = 0;
    while (!mbar_try(a, par)) { if (++it > 40000000u) TRAPV((a & 0xffffff) * 2 + par); }
}
DEV void mbar_wait_cl(uint32_t a, uint32_t par) { if (!mbar_try_cl(a, par)) mbar_wait_slow(a, par); }
DEV void bar_sync(int id, int n) { asm volatile("bar.sync %0, %1;" ::"r"(id), "r"(n) : "memory"); }
DEV void bar_arrive(int id, int n) { asm volatile("bar.arrive %0, %1;" ::"r"(id), "r"(n) : "memory"); }
DEV void cluster_arrive() { asm volatile("barrier.cluster.arrive.release.aligned;" ::: "memory"); }
DEV void cluster_wait() { asm volatile("barrier.cluster.wait.acquire.aligned;" ::: "memory"); }
DEV void fence_async_smem() { asm volatile("fence.proxy.async.shared::cta;" ::: "memory"); }
DEV void fence_async_all() { asm volatile("fence.proxy.async;" ::: "memory"); }
DEV void fence_async_gl() { asm volatile("fence.proxy.async.global;" ::: "memory"); }
DEV void fence_gpu() { asm volatile("fence.acq_rel.gpu;" ::: "memory"); }
DEV void fence_rel() { asm volatile("fence.release.gpu;" ::: "memory"); }

DEV unsigned ld_acq(const unsigned* p) { unsigned v; asm volatile("ld.acquire.gpu.global.u32 %0, [%1];" : "=r"(v) : "l"(p) : "memory"); return v; }
DEV unsigned ld_rlx(const unsigned* p) { unsigned v; asm volatile("ld.relaxed.gpu.global.u32 %0, [%1];" : "=r"(v) : "l"(p) : "memory"); return v; }
DEV unsigned atom_ar(unsigned* p) { unsigned v; asm volatile("atom.acq_rel.gpu.global.add.u32 %0, [%1], 1;" : "=r"(v) : "l"(p) : "memory"); return v; }
DEV void red_add(unsigned* p, unsigned v) { asm volatile("red.relaxed.gpu.global.add.u32 [%0], %1;" ::"l"(p), "r"(v) : "memory"); }
DEV void st_rlx(unsigned* p, unsigned v) { asm volatile("st.relaxed.gpu.global.u32 [%0], %1;" ::"l"(p), "r"(v) : "memory"); }
DEV uint4 ld_rlx4(const void* p) {
    uint4 v;
    asm volatile("ld.relaxed.gpu.global.v4.u32 {%0,%1,%2,%3}, [%4];" : "=r"(v.x), "=r"(v.y), "=r"(v.z), "=r"(v.w) : "l"(p) : "memory");
    return v;
}
DEV float2 ld_rlx_f2(const float* p) {
    float2 v;
    asm volatile("ld.relaxed.gpu.global.v2.f32 {%0,%1}, [%2];" : "=f"(v.x), "=f"(v.y) : "l"(p) : "memory");
    return v;
}
DEV void st_rlx4(void* p, uint4 v) { asm volatile("st.relaxed.gpu.global.v4.u32 [%0], {%1,%2,%3,%4};" ::"l"(p), "r"(v.x), "r"(v.y), "r"(v.z), "r"(v.w) : "memory"); }
DEV void st_rlx2(void* p, unsigned a, unsigned b) { asm volatile("st.relaxed.gpu.global.v2.u32 [%0], {%1,%2};" ::"l"(p), "r"(a), "r"(b) : "memory"); }
DEV void wait_cnt_slow(const unsigned* p, unsigned tgt, unsigned far) {
    long long t0 = clock64();
    while (true) {
        const int d = (int)(tgt - ld_acq(p));
        if (d <= 0) break;
        __nanosleep(d > 1 ? far : WSL);
        if (clock64() - t0 > TIMEOUT) TRAPV((int)((const char*)p - (const char*)&g_sync));
    }
}
DEV void wait_cnt(const unsigned* p, unsigned tgt, unsigned far = WSF) { if ((int)(ld_acq(p) - tgt) < 0) wait_cnt_slow(p, tgt, far); }

DEV void tma2d(uint32_t dst, const CUtensorMap* m, int c0, int c1, uint32_t bar) {
    asm volatile("cp.async.bulk.tensor.2d.shared::cluster.global.tile.mbarrier::complete_tx::bytes [%0], [%1, {%3, %4}], [%2];"
                 ::"r"(dst), "l"(m), "r"(bar), "r"(c0), "r"(c1) : "memory");
}
DEV void tma2d_mc(uint32_t dst, const CUtensorMap* m, int c0, int c1, uint32_t bar) {
    asm volatile("cp.async.bulk.tensor.2d.shared::cluster.global.tile.mbarrier::complete_tx::bytes.multicast::cluster [%0], [%1, {%3, %4}], [%2], %5;"
                 ::"r"(dst), "l"(m), "r"(bar), "r"(c0), "r"(c1), "h"((unsigned short)3) : "memory");
}
DEV void tma_store(const CUtensorMap* m, int c0, int c1, uint32_t src) {
    asm volatile("cp.async.bulk.tensor.2d.global.shared::cta.tile.bulk_group [%0, {%2, %3}], [%1];" ::"l"(m), "r"(src), "r"(c0), "r"(c1) : "memory");
}
DEV void tma_reduce(const CUtensorMap* m, int c0, int c1, uint32_t src) {
    asm volatile("cp.reduce.async.bulk.tensor.2d.global.shared::cta.add.tile.bulk_group [%0, {%2, %3}], [%1];" ::"l"(m), "r"(src), "r"(c0), "r"(c1) : "memory");
}
DEV void bulk_commit() { asm volatile("cp.async.bulk.commit_group;" ::: "memory"); }
template <int N> DEV void bulk_wait_read() { asm volatile("cp.async.bulk.wait_group.read %0;" ::"n"(N) : "memory"); }
DEV void bulk_wait_all() { asm volatile("cp.async.bulk.wait_group 0;" ::: "memory"); }
DEV void l2_line(const void* p) { asm volatile("prefetch.global.L2 [%0];" ::"l"(p) : "memory"); }
DEV void l2_prefetch(const void* p, uint32_t bytes) { asm volatile("cp.async.bulk.prefetch.L2.global [%0], %1;" ::"l"(p), "r"(bytes) : "memory"); }

DEV uint32_t pk(float lo, float hi) { uint32_t r; asm("cvt.rn.bf16x2.f32 %0, %1, %2;" : "=r"(r) : "f"(hi), "f"(lo)); return r; }
DEV uint32_t hadd2(uint32_t a, uint32_t b) { uint32_t r; asm("add.rn.bf16x2 %0, %1, %2;" : "=r"(r) : "r"(a), "r"(b)); return r; }
DEV uint32_t movm(uint32_t a) { uint32_t r; asm volatile("movmatrix.sync.aligned.m8n8.trans.b16 %0, %1;" : "=r"(r) : "r"(a)); return r; }
DEV float ex2(float x) { float r; asm("ex2.approx.ftz.f32 %0, %1;" : "=f"(r) : "f"(x)); return r; }
DEV void mma16(float* c, uint32_t a0, uint32_t a1, uint32_t a2, uint32_t a3, uint32_t b0, uint32_t b1) {
    asm volatile("mma.sync.aligned.m16n8k16.row.col.f32.bf16.bf16.f32 {%0,%1,%2,%3}, {%4,%5,%6,%7}, {%8,%9}, {%0,%1,%2,%3};"
                 : "+f"(c[0]), "+f"(c[1]), "+f"(c[2]), "+f"(c[3]) : "r"(a0), "r"(a1), "r"(a2), "r"(a3), "r"(b0), "r"(b1));
}
DEV void mma8(float* c, uint32_t a0, uint32_t a1, uint32_t b0) {
    asm volatile("mma.sync.aligned.m16n8k8.row.col.f32.bf16.bf16.f32 {%0,%1,%2,%3}, {%4,%5}, {%6}, {%0,%1,%2,%3};"
                 : "+f"(c[0]), "+f"(c[1]), "+f"(c[2]), "+f"(c[3]) : "r"(a0), "r"(a1), "r"(b0));
}
DEV void ldm4(uint32_t* r, uint32_t a) {
    asm volatile("ldmatrix.sync.aligned.m8n8.x4.shared.b16 {%0,%1,%2,%3}, [%4];" : "=r"(r[0]), "=r"(r[1]), "=r"(r[2]), "=r"(r[3]) : "r"(a) : "memory");
}
DEV void ldm4t(uint32_t* r, uint32_t a) {
    asm volatile("ldmatrix.sync.aligned.m8n8.x4.trans.shared.b16 {%0,%1,%2,%3}, [%4];" : "=r"(r[0]), "=r"(r[1]), "=r"(r[2]), "=r"(r[3]) : "r"(a) : "memory");
}
DEV void stm4(uint32_t a, uint32_t r0, uint32_t r1, uint32_t r2, uint32_t r3) {
    asm volatile("stmatrix.sync.aligned.m8n8.x4.shared.b16 [%0], {%1,%2,%3,%4};" ::"r"(a), "r"(r0), "r"(r1), "r"(r2), "r"(r3) : "memory");
}
DEV void stm4t(uint32_t a, uint32_t r0, uint32_t r1, uint32_t r2, uint32_t r3) {
    asm volatile("stmatrix.sync.aligned.m8n8.x4.trans.shared.b16 [%0], {%1,%2,%3,%4};" ::"r"(a), "r"(r0), "r"(r1), "r"(r2), "r"(r3) : "memory");
}
DEV void sts4f(uint32_t a, const float* v) { asm volatile("st.shared.v4.f32 [%0], {%1,%2,%3,%4};" ::"r"(a), "f"(v[0]), "f"(v[1]), "f"(v[2]), "f"(v[3]) : "memory"); }
DEV unsigned clk32() { unsigned long long t; asm volatile("mov.u64 %0, %%clock64;" : "=l"(t) :: "memory"); return (unsigned)t; }
DEV void sched_fence(uint32_t nz, int c) { asm volatile("{ .reg .pred p; setp.eq.u32 p, %0, %1; @p trap; }" ::"r"(nz), "r"(c) : "memory"); }
DEV void keep4(uint32_t nz, uint4 v) {
    asm volatile("{ .reg .pred p; setp.eq.u32 p, %0, 99; @p st.shared.v4.u32 [%0], {%1,%2,%3,%4}; }" ::"r"(nz), "r"(v.x), "r"(v.y), "r"(v.z), "r"(v.w) : "memory");
}
#define PIN(x) asm volatile("" : "+r"(x))
#define PINL(x) asm volatile("" : "+l"(x))
DEV float ex2v(float x) { float r; asm volatile("ex2.approx.ftz.f32 %0, %1;" : "=f"(r) : "f"(x)); return r; }
DEV uint4 lds4(uint32_t a) { uint4 v; asm volatile("ld.shared.v4.u32 {%0,%1,%2,%3}, [%4];" : "=r"(v.x), "=r"(v.y), "=r"(v.z), "=r"(v.w) : "r"(a) : "memory"); return v; }
DEV uint4 lds4v(uint32_t a) { uint4 v; asm volatile("ld.volatile.shared.v4.u32 {%0,%1,%2,%3}, [%4];" : "=r"(v.x), "=r"(v.y), "=r"(v.z), "=r"(v.w) : "r"(a) : "memory"); return v; }
DEV float4 lds4f(uint32_t a) { float4 v; asm volatile("ld.shared.v4.f32 {%0,%1,%2,%3}, [%4];" : "=f"(v.x), "=f"(v.y), "=f"(v.z), "=f"(v.w) : "r"(a) : "memory"); return v; }
DEV uint32_t lds1(uint32_t a) { uint32_t v; asm volatile("ld.shared.u32 %0, [%1];" : "=r"(v) : "r"(a) : "memory"); return v; }
DEV uint2 lds2(uint32_t a) { uint2 v; asm volatile("ld.shared.v2.u32 {%0,%1}, [%2];" : "=r"(v.x), "=r"(v.y) : "r"(a) : "memory"); return v; }
DEV char* ldsp(uint32_t a) { char* v; asm volatile("ld.shared.u64 %0, [%1];" : "=l"(v) : "r"(a) : "memory"); return v; }
DEV void stsp(uint32_t a, char* v) { asm volatile("st.shared.u64 [%0], %1;" ::"r"(a), "l"(v) : "memory"); }
DEV void sts4(uint32_t a, uint4 v) { asm volatile("st.shared.v4.u32 [%0], {%1,%2,%3,%4};" ::"r"(a), "r"(v.x), "r"(v.y), "r"(v.z), "r"(v.w) : "memory"); }
DEV void sts2(uint32_t a, uint32_t x, uint32_t y) { asm volatile("st.shared.v2.u32 [%0], {%1,%2};" ::"r"(a), "r"(x), "r"(y) : "memory"); }
DEV void sts2f(uint32_t a, float x, float y) { asm volatile("st.shared.v2.f32 [%0], {%1,%2};" ::"r"(a), "f"(x), "f"(y) : "memory"); }
DEV void sts1(uint32_t a, uint32_t x) { asm volatile("st.shared.u32 [%0], %1;" ::"r"(a), "r"(x) : "memory"); }
DEV void sts_cl2(uint32_t a, uint32_t x, uint32_t y) { asm volatile("st.shared::cluster.v2.u32 [%0], {%1,%2};" ::"r"(a), "r"(x), "r"(y) : "memory"); }
DEV void st_async2(uint32_t a, float x, float y, uint32_t bar) {
    asm volatile("st.async.weak.shared::cluster.mbarrier::complete_tx::bytes.v2.f32 [%0], {%1,%2}, [%3];" ::"r"(a), "f"(x), "f"(y), "r"(bar) : "memory");
}
DEV void st_async4(uint32_t a, uint4 v, uint32_t bar) {
    asm volatile("st.async.weak.shared::cluster.mbarrier::complete_tx::bytes.v4.u32 [%0], {%1,%2,%3,%4}, [%5];"
                 ::"r"(a), "r"(v.x), "r"(v.y), "r"(v.z), "r"(v.w), "r"(bar) : "memory");
}
DEV uint32_t lds1v(uint32_t a) { uint32_t v; asm volatile("ld.volatile.shared.u32 %0, [%1];" : "=r"(v) : "r"(a) : "memory"); return v; }
DEV void wg_fence() { asm volatile("wgmma.fence.sync.aligned;" ::: "memory"); }
DEV void wg_commit() { asm volatile("wgmma.commit_group.sync.aligned;" ::: "memory"); }
template <int N> DEV void wg_wait() { asm volatile("wgmma.wait_group.sync.aligned %0;" ::"n"(N) : "memory"); }
DEV uint64_t mkdesc(uint32_t addr, uint32_t lbo, uint32_t sbo, uint32_t sw) {
    return (uint64_t)((addr & 0x3FFFF) >> 4) | ((uint64_t)(lbo >> 4) << 16) | ((uint64_t)(sbo >> 4) << 32) | ((uint64_t)sw << 62);
}
#define R8(b) "+f"(d[b]), "+f"(d[b + 1]), "+f"(d[b + 2]), "+f"(d[b + 3]), "+f"(d[b + 4]), "+f"(d[b + 5]), "+f"(d[b + 6]), "+f"(d[b + 7])
DEV void wgmma256(float* d, uint64_t da, uint64_t db, int acc) {
    asm volatile(
        "{ .reg .pred p; setp.ne.b32 p, %130, 0;\n"
        "wgmma.mma_async.sync.aligned.m64n256k16.f32.bf16.bf16 {"
        "%0,%1,%2,%3,%4,%5,%6,%7,%8,%9,%10,%11,%12,%13,%14,%15,%16,%17,%18,%19,%20,%21,%22,%23,%24,%25,%26,%27,%28,%29,%30,%31,"
        "%32,%33,%34,%35,%36,%37,%38,%39,%40,%41,%42,%43,%44,%45,%46,%47,%48,%49,%50,%51,%52,%53,%54,%55,%56,%57,%58,%59,%60,%61,%62,%63,"
        "%64,%65,%66,%67,%68,%69,%70,%71,%72,%73,%74,%75,%76,%77,%78,%79,%80,%81,%82,%83,%84,%85,%86,%87,%88,%89,%90,%91,%92,%93,%94,%95,"
        "%96,%97,%98,%99,%100,%101,%102,%103,%104,%105,%106,%107,%108,%109,%110,%111,%112,%113,%114,%115,%116,%117,%118,%119,%120,%121,%122,%123,%124,%125,%126,%127"
        "}, %128, %129, p, 1, 1, 0, 1; }\n"
        : R8(0), R8(8), R8(16), R8(24), R8(32), R8(40), R8(48), R8(56), R8(64), R8(72), R8(80), R8(88), R8(96), R8(104), R8(112), R8(120)
        : "l"(da), "l"(db), "r"(acc));
}
DEV void wgmma8(float* d, uint64_t da, uint64_t db, int acc) {
    asm volatile("{ .reg .pred p; setp.ne.b32 p, %6, 0;\n"
                 "wgmma.mma_async.sync.aligned.m64n8k16.f32.bf16.bf16 {%0,%1,%2,%3}, %4, %5, p, 1, 1, 1, 0; }\n"
                 : "+f"(d[0]), "+f"(d[1]), "+f"(d[2]), "+f"(d[3]) : "l"(da), "l"(db), "r"(acc));
}

DEV void wgmma8_first(float* d, uint64_t da, uint64_t db) {
    asm volatile("{ .reg .pred p; setp.ne.b32 p, 0, 0;\n"
                 "wgmma.mma_async.sync.aligned.m64n8k16.f32.bf16.bf16 {%0,%1,%2,%3}, %4, %5, p, 1, 1, 1, 0; }\n"
                 : "=f"(d[0]), "=f"(d[1]), "=f"(d[2]), "=f"(d[3]) : "l"(da), "l"(db));
}

constexpr float SCALE_LOG2E = 0.08838834764831845f * 1.4426950408889634f;

#define D1 25
#define DG1 120
#define D2 60
#define NPROBE 3
#define OSM 1
#define VOV 2
DEV void cpa16(uint32_t d, const void* g) { asm volatile("cp.async.cg.shared.global [%0], [%1], 16;" ::"r"(d), "l"(g) : "memory"); }
DEV void cpa_commit() { asm volatile("cp.async.commit_group;" ::: "memory"); }
template <int N> DEV void cpa_wait() { asm volatile("cp.async.wait_group %0;" ::"n"(N) : "memory"); }
DEV void delay(unsigned t0, unsigned d) { while (clk32() - t0 < d) {} }
DEV void mma16z(float* c, const uint32_t* a, uint32_t b0, uint32_t b1) {
    asm volatile("mma.sync.aligned.m16n8k16.row.col.f32.bf16.bf16.f32 {%0,%1,%2,%3}, {%4,%5,%6,%7}, {%8,%9}, {%10,%10,%10,%10};"
                 : "=f"(c[0]), "=f"(c[1]), "=f"(c[2]), "=f"(c[3]) : "r"(a[0]), "r"(a[1]), "r"(a[2]), "r"(a[3]), "r"(b0), "r"(b1), "f"(0.f));
}
DEV void mma16a(float* c, const uint32_t* a, uint32_t b0, uint32_t b1) { mma16(c, a[0], a[1], a[2], a[3], b0, b1); }
DEV void mma16z4(float* c, uint32_t a0, uint32_t a1, uint32_t a2, uint32_t a3, uint32_t b0, uint32_t b1) {
    const uint32_t a[4] = {a0, a1, a2, a3};
    mma16z(c, a, b0, b1);
}
DEV void mmaz(float* c, uint4 a, uint32_t b0, uint32_t b1) { mma16z4(c, a.x, a.y, a.z, a.w, b0, b1); }
DEV void mmaa(float* c, uint4 a, uint32_t b0, uint32_t b1) { mma16(c, a.x, a.y, a.z, a.w, b0, b1); }
template <int FIRST> DEV void wgmma32(float* d, uint4 a, uint32_t db) {
    if (FIRST)
        asm volatile("{ .reg .pred p; .reg .b64 dd; setp.ne.b32 p, 0, 0; mov.b64 dd, {%20, 0x40000040};\n"
                     "wgmma.mma_async.sync.aligned.m64n32k16.f32.bf16.bf16 {%0,%1,%2,%3,%4,%5,%6,%7,%8,%9,%10,%11,%12,%13,%14,%15}, {%16,%17,%18,%19}, dd, p, 1, 1, 0; }\n"
                     : "=f"(d[0]), "=f"(d[1]), "=f"(d[2]), "=f"(d[3]), "=f"(d[4]), "=f"(d[5]), "=f"(d[6]), "=f"(d[7]),
                       "=f"(d[8]), "=f"(d[9]), "=f"(d[10]), "=f"(d[11]), "=f"(d[12]), "=f"(d[13]), "=f"(d[14]), "=f"(d[15])
                     : "r"(a.x), "r"(a.y), "r"(a.z), "r"(a.w), "r"(db));
    else
        asm volatile("{ .reg .b64 dd; mov.b64 dd, {%20, 0x40000040};\n"
                     "wgmma.mma_async.sync.aligned.m64n32k16.f32.bf16.bf16 {%0,%1,%2,%3,%4,%5,%6,%7,%8,%9,%10,%11,%12,%13,%14,%15}, {%16,%17,%18,%19}, dd, 1, 1, 1, 0; }\n"
                     : R8(0), R8(8) : "r"(a.x), "r"(a.y), "r"(a.z), "r"(a.w), "r"(db));
}
template <int O> DEV void st_async4o(uint32_t a, uint4 v, uint32_t bar) {
    asm volatile("st.async.weak.shared::cluster.mbarrier::complete_tx::bytes.v4.u32 [%0+%6], {%1,%2,%3,%4}, [%5];"
                 ::"r"(a), "r"(v.x), "r"(v.y), "r"(v.z), "r"(v.w), "r"(bar), "n"(O) : "memory");
}
template <int O> DEV void st_async2o(uint32_t a, uint32_t x, uint32_t y, uint32_t bar) {
    asm volatile("st.async.weak.shared::cluster.mbarrier::complete_tx::bytes.v2.u32 [%0+%4], {%1,%2}, [%3];" ::"r"(a), "r"(x), "r"(y), "r"(bar), "n"(O) : "memory");
}
DEV void sts1v(uint32_t a, uint32_t x) { asm volatile("st.volatile.shared.u32 [%0], %1;" ::"r"(a), "r"(x) : "memory"); }
DEV uint32_t anchor(uint32_t d, uint32_t z, uint32_t a) { uint32_t r; asm volatile("lop3.b32 %0, %1, %2, %3, 0x6a;" : "=r"(r) : "r"(d), "r"(z), "r"(a)); return r; }
DEV void st_rlx2_if(uint32_t c, void* p, uint32_t a, uint32_t b) {
    asm volatile("{ .reg .pred p; setp.ne.u32 p, %0, 0; @p st.relaxed.gpu.global.v2.u32 [%1], {%2,%3}; }" ::"r"(c), "l"(p), "r"(a), "r"(b) : "memory");
}
DEV void ld_miss1(uint4& v, const void* p) {
    asm volatile("{ .reg .pred p; setp.eq.u32 p, %0, 0xffffffff; @p ld.relaxed.gpu.global.v4.u32 {%0,%1,%2,%3}, [%4]; }" : "+r"(v.x), "+r"(v.y), "+r"(v.z), "+r"(v.w) : "l"(p) : "memory");
}
DEV uint2 lds2v(uint32_t a) { uint2 v; asm volatile("ld.volatile.shared.v2.u32 {%0,%1}, [%2];" : "=r"(v.x), "=r"(v.y) : "r"(a) : "memory"); return v; }
DEV uint4 ldm4u(uint32_t a) { uint32_t r[4]; ldm4(r, a); return make_uint4(r[0], r[1], r[2], r[3]); }
DEV uint4 ldm4tu(uint32_t a) { uint32_t r[4]; ldm4t(r, a); return make_uint4(r[0], r[1], r[2], r[3]); }
DEV void ld_miss(uint4& v, const void* p) {
    asm volatile("{ .reg .pred p, q; setp.eq.u32 q, %0, 0xffffffff; setp.eq.or.u32 p, %2, 0xffffffff, q;\n"
                 "@p ld.relaxed.gpu.global.v4.u32 {%0,%1,%2,%3}, [%4]; }" : "+r"(v.x), "+r"(v.y), "+r"(v.z), "+r"(v.w) : "l"(p) : "memory");
}
DEV float blo(uint32_t x) { return __uint_as_float(x << 16); }
DEV float bhi(uint32_t x) { return __uint_as_float(x & 0xffff0000u); }
DEV uint32_t sum4(uint32_t a, uint32_t b, uint32_t c, uint32_t d) {
    return pk((blo(a) + blo(b)) + (blo(c) + blo(d)), (bhi(a) + bhi(b)) + (bhi(c) + bhi(d)));
}
DEV uint32_t hsum4(uint32_t a, uint32_t b, uint32_t c, uint32_t d) { return hadd2(hadd2(a, b), hadd2(c, d)); }
DEV uint32_t div3(uint32_t s) { return (s * 171) >> 9; }
DEV uint32_t mod3(uint32_t s) { return s - 3 * div3(s); }
DEV void ring_fill(const Params& P, uint32_t sb, int me, int n) {
    const uint32_t st = mod3(n), bar = sb + B_KV + st * 8;
    asm volatile("{ .reg .pred p; elect.sync _|p, 0xffffffff;\n"
                 "@p mbarrier.arrive.expect_tx.shared::cta.b64 _, [%0], 12288;\n"
                 "@p cp.async.bulk.tensor.2d.shared::cluster.global.tile.mbarrier::complete_tx::bytes [%1], [%4, {%5, %8}], [%0];\n"
                 "@p cp.async.bulk.tensor.2d.shared::cluster.global.tile.mbarrier::complete_tx::bytes [%2], [%4, {%6, %8}], [%0];\n"
                 "@p cp.async.bulk.tensor.2d.shared::cluster.global.tile.mbarrier::complete_tx::bytes [%3], [%4, {%7, %8}], [%0]; }"
                 ::"r"(bar), "r"(sb + C_RV + st * 8192), "r"(sb + C_RV + st * 8192 + 4096), "r"(sb + C_RK + st * 4096), "l"(&P.m[M_KVC]),
                   "r"(4096 + me * 64), "r"(4096 + (me ^ 1) * 64), "r"(me * 64), "r"(n * 32) : "memory");
}
DEV void wait_cnt_w(const unsigned* p, unsigned tgt) {
    unsigned it = 0;
    while (__any_sync(~0u, (int)(ld_rlx(p) - tgt) < 0)) { __nanosleep(40); if (++it > 8000000u) TRAPV((int)((const char*)p - (const char*)&g_sync)); }
}
DEV void mbar_arrive(uint32_t a) { asm volatile("mbarrier.arrive.shared::cta.b64 _, [%0];" ::"r"(a) : "memory"); }

DEV void chain_helper(const Params& P, uint32_t sb, int head, uint32_t rank, unsigned E, int warp, int lane) {
    {
    const int me = head * 2 + rank;
    const int tid = warp * 32 + lane;
    {
        uint4 sv = make_uint4(SENT, SENT, SENT, SENT);
        char* p = P.arena + (g1_base(me) + tid * 16);
#pragma unroll
        for (int s = 0; s < 3; s++) { st_rlx4(p + g1_slot(s), sv); st_rlx4(p + g1_slot(s) + 2048, sv); }
        if (lane < 8) {
            if (warp == 3) {
                const unsigned short* src = (const unsigned short*)P.mem0 + lane * DM + (me >> 2) * 32 + (me & 3) * 2;
                uint32_t w[4];
#pragma unroll
                for (int q = 0; q < 4; q++) {
                    const int gb = q >> 1, il = (q & 1) * 2;
                    const uint32_t lo = __ldg(src + il * 8 + gb), hi = __ldg(src + il * 8 + 8 + gb);
                    w[q] = (lo == 0xffffu ? 0x7fffu : lo) | (hi << 16);
                }
                sv = make_uint4(w[0], w[1], w[2], w[3]);
            }
            st_rlx4(P.arena + (g2_base(me) + g2_slot(warp) + lane * 16), sv);
        }
        fence_gpu();
        bar_sync(5, 128);
        if (tid == 0) { fence_gpu(); red_add(&g_sync.chain_ready, 1); }
    }
    {
        const uint32_t lw = sb + lane * 16 + warp * 512;
        const uint32_t g = lane >> 2, m = lane >> 3, jr = lane & 7;
        sts4(lw + C_T1, make_uint4((head * 256 + (warp >> 1) * 128 + (rank * 2 + (warp & 1)) * 32 + lane) * 16,
                                   sb + C_RK + ((m >> 1) * 8 + jr) * 128 + (((4 * (warp & 1) + (m & 1)) ^ jr) << 4),
                                   sb + C_QB + (m & 1) * 1024 + (m >> 1) * 128 + jr * 16 + (warp & 1) * 512,
                                   0));
        sts4(lw + C_T2, make_uint4(D1 + min(warp, 2) * DG1, g < 2 ? 0x00003f80u : (g < 4 ? 0x3f800000u : 0u),
                                   g1_base(me) + (lane & 3) * 128 + g * 16, g2_base(me) + ((g & 3) * 2 + (lane & 1)) * 16 + (g >> 2) * 8));
        sts4(sb + S_ONES + tid * 16, make_uint4(SENT, SENT, SENT, SENT));
        fence_async_smem();
        if (tid == 0) { sts4(sb + S_CH, make_uint4(me, (E + 1) * 8, 3, g1_base(me))); sts1(sb + S_DP, mapa(sb, rank ^ 1) - sb); }
    }
    bar_sync(4, 384);
    if (warp == 3) {
        wait_cnt_w(&g_sync.kv[0][(lane & 16) + (head >> 1)], (E + 1) * 8);
        fence_async_gl();
#pragma unroll 1
        for (int n = 0; n < 3; n++) ring_fill(P, sb, me, n);
    }
    if (warp == 0) {
        wait_cnt_w(&g_sync.chain_ready, (E + 1) * 64);
        fence_gpu();
        sts1v(sb + S_FLAG, 1);
    }
    }
    bar_sync(5, 128);
    sb = __shfl_sync(~0u, sb, 0);
    warp = __shfl_sync(~0u, warp, 0);
    uint32_t lw = __shfl_sync(~0u, sb + lane * 16 + warp * 512, lane);

#pragma unroll 1
    for (int s = 0; s < NSEG; s++) {
        PIN(lw);
        sb = (lw & ~1023u) - (warp & 2) * 512;
        const bool last = s == NSEG - 1;
        const uint32_t dp = lds1(sb + S_DP);
        if (warp >= 2) {
            const uint32_t vp = lw + (C_VP - 1024);
            char* ex = (char*)g_kvm + (lds1(lw + C_T1) + s * (NH * 4096));
            uint32_t ra = lw + dp + C_VF, rb = sb + dp + B_VR;
            PINL(ex); PIN(ra); PIN(rb);
            sched_fence(s, 2000);
            bar_sync(warp == 2 ? 3 : 10, 160);
            const uint4 v0 = ldm4tu(vp), v1 = ldm4tu(vp + 1024), v2 = ldm4tu(vp + 2048), v3 = ldm4tu(vp + 3072);
            const uint4 f = make_uint4(hsum4(v0.x, v1.x, v2.x, v3.x), hsum4(v0.y, v1.y, v2.y, v3.y), hsum4(v0.z, v1.z, v2.z, v3.z), hsum4(v0.w, v1.w, v2.w, v3.w));
            if (!last) {
                st_async4(ra, f, rb);
                sts4(lw + (C_VF - 1024), f);
                mbar_arrive_elect(sb + B_VL);
            }
            st_rlx4(ex, f);
            if (warp == 2) {
                const uint4 ch = lds4(sb + S_CH);
                if (s >= 1)
                    asm volatile("{ .reg .pred p; elect.sync _|p, 0xffffffff;\n"
                                 "@p cp.async.bulk.global.shared::cta.bulk_group [%0], [%2], 2048;\n"
                                 "@p cp.async.bulk.global.shared::cta.bulk_group [%0+2048], [%2], 2048;\n"
                                 "@p cp.async.bulk.global.shared::cta.bulk_group [%1], [%2], 128;\n"
                                 "cp.async.bulk.commit_group; }"
                                 ::"l"(P.arena + (ch.w + g1_slot(mod3(s + 2)))), "l"(P.arena + (g2_base(ch.x) + g2_slot(s + 2))), "r"(sb + S_ONES) : "memory");
                bar_sync(8, 128);
                fence_rel();
                st_rlx(&g_sync.prog[ch.x][0], ch.y * 8 - 63 + s);
                bulk_wait_all();
                continue;
            }
            bar_arrive(8, 128);
            if (last) break;
        } else {
            const uint4 t1 = lds4(lw + C_T1);
            const uint32_t qofs = t1.z;
            uint32_t ka[4], kb[4], kc[4], kd[4];
            const uint32_t sl = last ? 0 : mod3(s);
            const uint32_t kr = t1.y + sl * 4096;
            if (!last) {
                if (warp == 0) { mbar_expect_elect(sb + B_S, 2560); mbar_expect_elect(sb + B_VR, 1024); }
                mbar_wait(sb + B_KV + sl * 8, div3(s) & 1);
            }
            ldm4(ka, kr); ldm4(kb, kr + 2048);
            uint32_t ra = lw + dp + (lw & 512) * 2 - 1024;
            PIN(ra);
            sched_fence(s, 2001);
            bar_sync(2 - warp, 160);
            uint32_t q0[4], r0[4], q1[4], r1[4], k0[4], k1[4], k2[4], k3[4];
            ldm4(q0, qofs); ldm4(r0, qofs + 2048); ldm4(k0, qofs + 4096); ldm4(k1, qofs + 6144);
            ldm4(q1, qofs + 256); ldm4(r1, qofs + 2304); ldm4(k2, qofs + 4352); ldm4(k3, qofs + 6400);
            sched_fence(s, 2002);
#pragma unroll
            for (int i = 0; i < 4; i++) q0[i] = hadd2(q0[i], r0[i]);
            float c[5][4];
            mma16z(c[0], q0, ka[0], ka[1]); mma16z(c[1], q0, ka[2], ka[3]);
            ldm4(kc, kr ^ 32);
            const uint32_t m0 = hsum4(k0[0], k0[1], k1[0], k1[1]), m1 = hsum4(k0[2], k0[3], k1[2], k1[3]);
            mma16z(c[2], q0, kb[0], kb[1]); mma16z(c[3], q0, kb[2], kb[3]);
            ldm4(kd, (kr ^ 32) + 2048);
            mma16z(c[4], q0, m0, m1);
#pragma unroll
            for (int i = 0; i < 4; i++) q1[i] = hadd2(q1[i], r1[i]);
            const uint32_t m2 = hsum4(k2[0], k2[1], k3[0], k3[1]), m3 = hsum4(k2[2], k2[3], k3[2], k3[3]);
            sched_fence(s, 2003);
            mma16a(c[0], q1, kc[0], kc[1]); mma16a(c[1], q1, kc[2], kc[3]);
            mma16a(c[2], q1, kd[0], kd[1]); mma16a(c[3], q1, kd[2], kd[3]);
            mma16a(c[4], q1, m2, m3);
            float p[10];
#pragma unroll
            for (int n = 0; n < 5; n++) { p[2 * n] = c[n][0] + c[n][2]; p[2 * n + 1] = c[n][1] + c[n][3]; }
#define U(x) __float_as_uint(x)
            PIN(lw);
            sb = lw & ~1023u;
            if (!last) {
                const uint32_t rb = (ra & ~2047u) + (1024 + B_S);
                st_async4o<C_SB + 2560>(ra, make_uint4(U(p[0]), U(p[1]), U(p[2]), U(p[3])), rb);
                st_async4o<C_SB + 3072>(ra, make_uint4(U(p[4]), U(p[5]), U(p[6]), U(p[7])), rb);
                st_async2o<C_SB + 3584>(ra, U(p[8]), U(p[9]), rb);
                if (warp == 1) {
                    sts4(lw + (C_SB - 512), make_uint4(U(p[0]), U(p[1]), U(p[2]), U(p[3])));
                    sts4(lw + C_SB, make_uint4(U(p[4]), U(p[5]), U(p[6]), U(p[7])));
                    sts2(lw + (C_SB + 512), U(p[8]), U(p[9]));
                    bar_arrive(9, 64);
                }
            }
            { char* ex = (char*)g_kvm + (lds1v(lw + C_T1) + s * (NH * 4096)); st_rlx2(ex, m0, m1); st_rlx2(ex + 8, m2, m3); }
            bar_arrive(8, 128);
            if (last) break;
            if (warp == 0) {
            const uint32_t sl = lw + C_SB;
#define F(x) __uint_as_float(x)
            bar_sync(9, 64);
            {
                const uint4 u0 = lds4v(sl), u1 = lds4v(sl + 512);
                const uint2 u2 = lds2v(sl + 1024);
                p[0] += F(u0.x); p[1] += F(u0.y); p[2] += F(u0.z); p[3] += F(u0.w); p[4] += F(u1.x); p[5] += F(u1.y); p[6] += F(u1.z); p[7] += F(u1.w);
                p[8] += F(u2.x); p[9] += F(u2.y);
            }
            mbar_wait(sb + B_S, s & 1);
            {
                const uint4 u0 = lds4v(sl + 1536), w0 = lds4v(sl + 3072), u1 = lds4v(sl + 2048), w1 = lds4v(sl + 3584);
                const uint2 u2 = lds2v(sl + 2560), w2 = lds2v(sl + 4096);
                p[0] += F(u0.x) + F(w0.x); p[1] += F(u0.y) + F(w0.y); p[2] += F(u0.z) + F(w0.z); p[3] += F(u0.w) + F(w0.w);
                p[4] += F(u1.x) + F(w1.x); p[5] += F(u1.y) + F(w1.y); p[6] += F(u1.z) + F(w1.z); p[7] += F(u1.w) + F(w1.w);
                p[8] += F(u2.x) + F(w2.x); p[9] += F(u2.y) + F(w2.y);
            }
#undef F
            float m = fmaxf(fmaxf(fmaxf(p[0], p[1]), fmaxf(p[2], p[3])), fmaxf(fmaxf(p[4], p[5]), fmaxf(p[6], p[7])));
            m = fmaxf(m, fmaxf(p[8], p[9]));
            const float mb = -m * SCALE_LOG2E;
            const float m1 = __shfl_xor_sync(~0u, m, 1);
#pragma unroll
            for (int i = 0; i < 5; i++) p[i] = ex2v(fmaf(p[i], SCALE_LOG2E, mb));
            float mr = fmaxf(m, m1);
            const float m2 = __shfl_xor_sync(~0u, mr, 2);
#pragma unroll
            for (int i = 5; i < 10; i++) p[i] = ex2v(fmaf(p[i], SCALE_LOG2E, mb));
            mr = fmaxf(mr, m2);
            const float cf = ex2v((m - mr) * SCALE_LOG2E);
#pragma unroll
            for (int i = 0; i < 10; i++) p[i] *= cf;
            sts4(lw + C_PB, make_uint4(pk(p[0], p[1]), pk(p[2], p[3]), pk(p[4], p[5]), pk(p[6], p[7])));
            sts1(lw + C_PB + 512, pk(p[8], p[9]));
            mbar_arrive_elect(sb + B_P);
            }
        }
        {
            const uint4 t2 = lds4(lw + C_T2);
            const char* pp = P.arena + (t2.z + g1_slot(mod3(s)));
            uint32_t sel0 = (lw & 64) ? 0u : t2.y, sel1 = t2.y ^ sel0;
            char* g2w = P.arena + (t2.w + g2_slot(s));
            const uint32_t dl = t2.x;
            PINL(pp); PINL(g2w); PIN(sel0); PIN(sel1);
            sched_fence(s, 2004);
            bar_sync(11, 352);
            if (D1 || warp) {
                sched_fence(lds1v(sb + S_DP), 0);
                delay(clk32(), dl);
            }
            uint4 v[8];
#pragma unroll
            for (int i = 0; i < 8; i++) v[i] = ld_rlx4(pp + i * 512);
            unsigned it = 0;
            while (true) {
                float c0[4], c1[4];
                mmaz(c0, v[0], sel0, sel1);
                mmaz(c1, v[1], sel0, sel1);
#pragma unroll
                for (int i = 2; i < 8; i += 2) { mmaa(c0, v[i], sel0, sel1); mmaa(c1, v[i + 1], sel0, sel1); }
                const float u0 = c0[0] + c1[0], u1 = c0[1] + c1[1], u2 = c0[2] + c1[2], u3 = c0[3] + c1[3];
                bool ok = (u0 == u0) && (u2 == u2);
                st_rlx2_if(ok && !(lw & 32), g2w, pk(u0, u2), pk(u1, u3));
                if (!__all_sync(~0u, ok)) {
                    bool miss = false;
#pragma unroll
                    for (int i = 0; i < 8; i++) miss = miss || v[i].x == SENT;
                    if (__any_sync(~0u, miss)) {
                        if (lds1v(sb + S_FLAG) == s + 2) break;
                        if (++it > 4000000u) __trap();
#pragma unroll
                        for (int i = 0; i < 8; i++) ld_miss1(v[i], pp + i * 512);
                        continue;
                    }
                    st_rlx2_if(!(lw & 32), g2w, pk(u0, u2), pk(u1, u3));
                }
                sts1v(sb + S_FLAG, s + 2);
                break;
            }
        }
        if (warp == 3) {
            const uint4 ch = lds4(sb + S_CH);
            int nfill = ch.z;
#pragma unroll 1
            while (nfill < NSEG - 1 && nfill <= s + 3) {
                if ((nfill & 3) == 0) {
                    const unsigned* f = &g_sync.kv[nfill >> 2][(lw & 16) + (ch.x >> 2)];
                    if (nfill == s + 1) wait_cnt_w(f, ch.y);
                    else if (__any_sync(~0u, (int)(ld_rlx(f) - ch.y) < 0)) break;
                    fence_async_gl();
                }
                ring_fill(P, sb, ch.x, nfill);
                nfill++;
            }
            sts1(sb + S_CH + 8, nfill);
        }
    }
}

DEV void chain_compute(const Params& P, uint32_t sb, int head, uint32_t rank, unsigned E, int cw, int lane) {
    uint32_t lw = sb + lane * 16 + cw * 512;
    sched_fence(P.zs[64] | P.zs[80] | P.zs[95], 1);
    uint4 wq[4][2][2], wk[4][2][2], wv[4][2][2], wo[8][2];
#define WLOAD(w, p, a) do { w[p][0][0] = ldm4tu((a) + ((p) & 1) * 2048); w[p][0][1] = ldm4tu(((a) ^ 32) + ((p) & 1) * 2048); \
        w[p][1][0] = ldm4tu((a) + ((p) & 1) * 2048 + 4096); w[p][1][1] = ldm4tu(((a) ^ 32) + ((p) & 1) * 2048 + 4096); } while (0)
#define WSAVE(w, o) do { _Pragma("unroll") for (int i = 0; i < 8; i++) sts4(lw + (o) + i * 4096, w[i >> 2][(i >> 1) & 1][i & 1]); } while (0)
#define WGET(w, o) do { _Pragma("unroll") for (int i = 0; i < 8; i++) w[i >> 2][(i >> 1) & 1][i & 1] = lds4v(lw + (o) + i * 4096); } while (0)
    {
        const int g = lane >> 2, t = lane & 3, eh = cw & 1, kq = cw >> 1;
        const int m = lane >> 3, jr = lane & 7;
        const uint32_t wl = sb + kq * 8192 + (8 * (m >> 1) + jr) * 128 + (((4 * eh + (m & 1)) ^ jr) << 4);
        const uint32_t wa = wl + eh * 32768, wb = wl + (eh ^ 1) * 32768;
        sts4(lw + C_TA, make_uint4(g1_base(32 * rank + 4 * cw + (g >> 1)) + head * 128 + jr * 16, g2_base(8 * cw) + t * 128 + g * 16,
                                   (eh ? 4 : 12) + kq, (eh ? 12 : 4) + kq));
        const int sr = cw * 4 + (lane >> 3);
        const uint32_t cd = sb + sr * 128 + ((jr ^ (sr & 7)) << 4);
        const size_t co = (size_t)(8 * (sr & 1) + (sr & 6) + 16 * (sr >> 3)) * 8192 + (head * DH + rank * 64) * 2 + jr * 16;
#define WSTAGE(w, o) do { const char* src = (const char*)(w) + co; _Pragma("unroll") for (int L = 0; L < 16; L++) \
            cpa16(cd + (o) + L * 4096, src + (16 * ((L & 6) * 4 + (L >> 3) * 4) + (L & 1)) * 8192); cpa_commit(); } while (0)
        WSTAGE(P.w[1], 65536); WSTAGE(P.w[0], 0); WSTAGE(P.w[2], 131072);
        cpa_wait<2>();
        bar_sync(6, 256);
        WLOAD(wv, 0, wa + 65536); WLOAD(wv, 1, wa + 65536); WLOAD(wv, 2, wb + 65536); WLOAD(wv, 3, wb + 65536);
        bar_sync(6, 256);
        {
            const char* src = (const char*)P.w[3] + (size_t)(head * DH + sr) * 1024 + rank * 512 + jr * 16;
#pragma unroll
            for (int L = 0; L < 16; L++)
                cpa16(cd + C_WO + L * 4096, src + ((((L >> 3) ^ rank) * 64 + (L & 1) * 32) * 1024 + ((L >> 1) & 3) * 128));
            cpa_commit();
        }
        cpa_wait<2>();
        bar_sync(6, 256);
        WLOAD(wk, 0, wa); WLOAD(wk, 1, wa); WLOAD(wk, 2, wb); WLOAD(wk, 3, wb);
        cpa_wait<1>();
        bar_sync(6, 256);
        WSAVE(wk, C_FK);
        WLOAD(wq, 0, wa + 131072); WLOAD(wq, 1, wa + 131072); WLOAD(wq, 2, wb + 131072); WLOAD(wq, 3, wb + 131072);
        WSAVE(wq, C_FQ);
        fence_async_smem();
        bar_arrive(4, 384);
        cpa_wait<0>();
        bar_sync(6, 256);
#pragma unroll
        for (int ks = 0; ks < 8; ks++) {
            wo[ks][0] = ldm4tu(wl + C_WO + (ks >> 2) * 32768 + (ks & 3) * 2048);
            wo[ks][1] = ldm4tu((wl ^ 32) + C_WO + (ks >> 2) * 32768 + (ks & 3) * 2048);
        }
        bar_sync(6, 256);
#pragma unroll
        for (int i = 0; i < 16; i++) sts4(lw + C_WO + i * 4096, wo[i >> 1][i & 1]);
    }
    sb = __shfl_sync(~0u, sb, 0);
    lw = __shfl_sync(~0u, lw, lane);

    bool kvok = false;
#pragma unroll 1
    for (int s = 0;; s++) {
#define VOG(mt) do { wg_fence(); wgmma32<1>(c, wo[7][mt], db + 262); \
            _Pragma("unroll") for (int ks = 6; ks >= 0; ks--) wgmma32<0>(c, wo[ks][mt], db + (ks >> 2) * 256 + (ks & 3) * 2); wg_commit(); } while (0)
#define VOST(o) do { sts4(lw + C_VO + (o), make_uint4(pk(c[0], c[1]), pk(c[2], c[3]), pk(c[4], c[5]), pk(c[6], c[7]))); \
            sts4(lw + C_VO + (o) + 4096, make_uint4(pk(c[8], c[9]), pk(c[10], c[11]), pk(c[12], c[13]), pk(c[14], c[15]))); } while (0)
#define WOL(i) wo[(i) >> 1][(i) & 1] = lds4v(lw + C_WO + (i) * 4096)
#define WQL(i) wq[(i) >> 2][((i) >> 1) & 1][(i) & 1] = lds4v(lw + C_FQ + (i) * 4096)
#define WKL(i) wk[(i) >> 2][((i) >> 1) & 1][(i) & 1] = lds4v(lw + C_FK + (i) * 4096)
#define FEN(c) sched_fence(s, 1000 + (c))
#define ANC(d, i) anchor(d, P.zs[64 + (i)], lw)
#define WOD(i, d) wo[(i) >> 1][(i) & 1] = lds4v(ANC(d, i) + C_WO + (i) * 4096)
#define WQD(i, d) wq[(i) >> 2][((i) >> 1) & 1][(i) & 1] = lds4v(ANC(d, 16 + (i)) + C_FQ + (i) * 4096)
#define WKD(i, d) wk[(i) >> 2][((i) >> 1) & 1][(i) & 1] = lds4v(ANC(d, 24 + (i)) + C_FK + (i) * 4096)
#define WQX(i) wq[(i) >> 2][((i) >> 1) & 1][(i) & 1].x
#define WKX(i) wk[(i) >> 2][((i) >> 1) & 1][(i) & 1].x
#define WOX(i) wo[(i) >> 1][(i) & 1].x
#define FU(x) __float_as_uint(x)
        const uint32_t sl = mod3(s);
        {
            const uint32_t db = __shfl_sync(~0u, (((sb + C_RV) & 0x3ffff) >> 4) + 0x10000 + sl * 512, 0);
            float c[16];
            if (!kvok) mbar_wait(sb + B_KV + sl * 8, div3(s) & 1);
            VOG(0);
            FEN(30);
            WOL(7); WOL(5); WOD(3, WOX(7)); WOD(1, WOX(5));
            wg_wait<0>();
            VOST(0);
            VOG(1);
            FEN(31);
            WQL(0); WQL(1);
#pragma unroll
            for (int i = 2; i < 8; i++) WQD(i, WQX(i - 2));
            FEN(32);
            wg_wait<0>();
            VOST(8192);
        }
        uint4 b0, b1, b2, b3;
        {
            float q[2][4], k[2][4];
#define G2OFS (((5u << 18) + 0x1000u + g2_slot(s + 3)) + ((((lw - sb) & 0xe00u) << 1) | ((lw & 0x30u) << 3) | ((lw & 0x1c0u) >> 2)))
            const char* pp = P.arena + G2OFS;
            PINL(pp);
            { unsigned it = 0; while (lds1v(sb + S_FLAG) != s + 1) { if (++it > 40000000u) __trap(); } }
            const unsigned t0 = clk32();
            delay(t0, D2);
            b0 = ld_rlx4(pp); b1 = ld_rlx4(pp + 512);
            WGET(wk, C_FK);
            const uint2 bid = lds2v(lw + C_TA + 8);
            FEN(4);
#define M2(c, w, p, kk, x, y) do { mmaa(c[0], w[p][kk][0], x, y); mmaa(c[1], w[p][kk][1], x, y); } while (0)
#define M2Z(c, w, x, y) do { mmaz(c[0], w[0][0][0], x, y); mmaz(c[1], w[0][0][1], x, y); } while (0)
#define QK(p, kk, x, y) do { M2(q, wq, p, kk, x, y); M2(k, wk, p, kk, x, y); } while (0)
#define FULL(a, b) __all_sync(~0u, max(max(a.x, a.z), max(b.x, b.z)) != SENT)
            sts4(lw + C_MEM, b0);
            sts4(lw + C_MEM + 4096, b1);
            M2Z(q, wq, b0.x, b0.y);
            const bool ok = FULL(b0, b1);
            if (!ok) {
                PIN(lw);
                unsigned it = 0;
                {
                    const char* p2 = P.arena + G2OFS;
                    do {
                        if (++it > 8000000u) __trap();
                        ld_miss(b0, p2); ld_miss(b1, p2 + 512);
                    } while (!FULL(b0, b1));
                }
                sts4(lw + C_MEM, b0); sts4(lw + C_MEM + 4096, b1);
                M2Z(q, wq, b0.x, b0.y);
            }
            bar_arrive(bid.x, 64);
            M2Z(k, wk, b0.x, b0.y);
            QK(0, 1, b0.z, b0.w);
            QK(1, 0, b1.x, b1.y);
            FEN(21);
            bar_sync(bid.y, 64);
            b2 = lds4v((lw ^ 512) + C_MEM); b3 = lds4v((lw ^ 512) + C_MEM + 4096);
            FEN(22);
            QK(1, 1, b1.z, b1.w);
            WOL(0);
            FEN(23);
            QK(2, 0, b2.x, b2.y);
            WOL(1); WOL(2);
            FEN(24);
            QK(2, 1, b2.z, b2.w);
            WOL(3); WOL(4);
            FEN(25);
            QK(3, 0, b3.x, b3.y);
            QK(3, 1, b3.z, b3.w);
            stm4t(lw + C_QB, pk(q[0][0], q[0][1]), pk(q[0][2], q[0][3]), pk(q[1][0], q[1][1]), pk(q[1][2], q[1][3]));
            stm4t(lw + C_KB, pk(k[0][0], k[0][1]), pk(k[0][2], k[0][3]), pk(k[1][0], k[1][1]), pk(k[1][2], k[1][3]));
            bar_arrive((lw & 512) ? 1 : 2, 160);
            FEN(3);
        }
        {
            float v[2][2][4];
            mmaz(v[0][0], wv[0][0][0], b0.x, b0.y); mmaz(v[0][1], wv[0][0][1], b0.x, b0.y);
            mmaz(v[1][0], wv[0][1][0], b0.z, b0.w); mmaz(v[1][1], wv[0][1][1], b0.z, b0.w);
#define VV(p, b) do { mmaa(v[0][0], wv[p][0][0], b.x, b.y); mmaa(v[0][1], wv[p][0][1], b.x, b.y); mmaa(v[1][0], wv[p][1][0], b.z, b.w); mmaa(v[1][1], wv[p][1][1], b.z, b.w); } while (0)
            VV(1, b1); VV(2, b2);
            FEN(26);
            WOL(5); WOL(6);
            FEN(27);
            VV(3, b3);
            stm4(lw + C_VP, pk(v[0][0][0] + v[1][0][0], v[0][0][1] + v[1][0][1]), pk(v[0][0][2] + v[1][0][2], v[0][0][3] + v[1][0][3]),
                 pk(v[0][1][0] + v[1][1][0], v[0][1][1] + v[1][1][1]), pk(v[0][1][2] + v[1][1][2], v[0][1][3] + v[1][1][3]));
            bar_arrive((lw & 512) ? 10 : 3, 160);
            WOD(7, FU(v[1][1][0]));
        }
        if (s == NSEG - 1) break;
        {
            const uint32_t l16 = sb + (lw & 496);
            WOD(8, WOX(7)); WOD(9, WOX(8)); WOD(10, WOX(9)); WOD(11, WOX(10));
            float m[2][4], n[2][4];
            kvok = s == NSEG - 2 || __all_sync(~0u, mbar_test(sb + B_KV + mod3(s + 1) * 8, div3(s + 1) & 1));
            mbar_wait(sb + B_VL, s & 1);
            {
                const uint4 f0 = lds4v(l16 + C_VF), f1 = lds4v(l16 + C_VF + 512);
                mmaz(m[0], wo[0][0], f0.x, f0.y); mmaz(m[1], wo[0][1], f0.x, f0.y);
                WOD(12, f1.x);
                mmaz(n[0], wo[1][0], f0.z, f0.w); mmaz(n[1], wo[1][1], f0.z, f0.w);
                WOD(13, FU(m[0][0]));
                mmaa(m[0], wo[2][0], f1.x, f1.y); mmaa(m[1], wo[2][1], f1.x, f1.y);
                WOD(14, FU(n[1][0]));
                mmaa(n[0], wo[3][0], f1.z, f1.w); mmaa(n[1], wo[3][1], f1.z, f1.w);
                WOD(15, FU(m[0][0]));
            }
            FEN(10);
            char* d = P.arena + (lds1v(lw + C_TA) + g1_slot(sl));
            PINL(d);
            uint4 vo0, vo1, vo2, vo3;
            vo0 = lds4v(lw + C_VO);
            vo2 = lds4v(lw + C_VO + 8192);
            mbar_wait(sb + B_VR, s & 1);
            {
                const uint4 f0 = lds4v(l16 + C_VF + 1024), f1 = lds4v(l16 + C_VF + 1536);
                FEN(11);
                mmaa(m[0], wo[4][0], f0.x, f0.y); mmaa(m[1], wo[4][1], f0.x, f0.y);
                mmaa(n[0], wo[5][0], f0.z, f0.w); mmaa(n[1], wo[5][1], f0.z, f0.w);
                mmaa(m[0], wo[6][0], f1.x, f1.y); mmaa(m[1], wo[6][1], f1.x, f1.y);
                mmaa(n[0], wo[7][0], f1.z, f1.w); mmaa(n[1], wo[7][1], f1.z, f1.w);
            }
            uint32_t x0 = pk(m[0][0] + n[0][0], m[0][1] + n[0][1]), x1 = pk(m[0][2] + n[0][2], m[0][3] + n[0][3]);
            uint32_t x2 = pk(m[1][0] + n[1][0], m[1][1] + n[1][1]), x3 = pk(m[1][2] + n[1][2], m[1][3] + n[1][3]);
            PIN(x0); PIN(x1); PIN(x2); PIN(x3);
            FEN(13);
            vo1 = lds4v(lw + C_VO + 4096);
            vo3 = lds4v(lw + C_VO + 12288);
            mbar_wait(sb + B_P, s & 1);
            const uint4 pf = lds4v(l16 + C_PB);
            const uint32_t pm = lds1v(l16 + C_PB + 512);
            float a[2][4], su[4];
            const uint32_t one = 0x3f803f80u;
            mma16z4(su, one, one, one, one, pf.x, pf.y);
            mmaz(a[0], vo0, pf.x, pf.y); mmaz(a[1], vo2, pf.x, pf.y);
            mma16(su, one, one, one, one, pf.z, pf.w);
            mmaa(a[0], vo1, pf.z, pf.w); mmaa(a[1], vo3, pf.z, pf.w);
            mma8(su, one, one, pm);
            mma8(a[0], x0, x1, pm);
            mma8(a[1], x2, x3, pm);
            float i0, i1;
            asm volatile("rcp.approx.ftz.f32 %0, %1;" : "=f"(i0) : "f"(su[0]));
            asm volatile("rcp.approx.ftz.f32 %0, %1;" : "=f"(i1) : "f"(su[1]));
            st_rlx4(d, make_uint4(pk(a[0][0] * i0, a[0][1] * i1), pk(a[0][2] * i0, a[0][3] * i1), pk(a[1][0] * i0, a[1][1] * i1), pk(a[1][2] * i0, a[1][3] * i1)));
            bar_arrive(11, 352);
        }
    }
}

DEV void bulk_producer(const Params& P, uint32_t sb, uint32_t rank, unsigned E, int first) {
    uint32_t st = 0, ph = 1;
    const uint32_t tempty0 = mapa(sb + B_TEMPTY, 0);
    unsigned* tick = &g_sync.task[E & 3];
    bool hold = false;
#pragma unroll 1
    for (int n = 0;; n++) {
        uint2 tk;
        if (rank == 0) {
            if (hold) mbar_wait_cl(sb + B_TEMPTY + ((n - 1) & 1) * 8, ((n - 1) >> 1) & 1);
            if (n == 0 && first >= 0) tk = make_uint2(T_A | (first >> 5) << 4 | (first & 31) << 8 | 8 << 20 | 1 << 27 | 1 << 28, 0);
            else {
                const unsigned t = atomicAdd(tick, 1) + (NPAIR - 32);
                tk = t < NTASK ? __ldg(&g_tasks[t]) : make_uint2(T_END, 0);
            }
            mbar_wait_cl(sb + B_TEMPTY + (n & 1) * 8, ((n >> 1) & 1) ^ 1);
            bcast2(sb + S_TASK + (n & 1) * 8, sb + B_TFULL + (n & 1) * 8, tk.x, tk.y);
        } else {
            mbar_wait_cl(sb + B_TFULL + (n & 1) * 8, (n >> 1) & 1);
            tk.x = lds1(sb + S_TASK + (n & 1) * 8); tk.y = lds1(sb + S_TASK + (n & 1) * 8 + 4);
            mbar_arrive_cl(tempty0 + (n & 1) * 8);
        }
        const int type = tk.x & 7;
        if (type == T_END) break;
        hold = (type == T_B || type == T_D) && ((tk.x >> 4) & 15) >= HOLD;
        const int shareA = (tk.x >> 3) & 1;
        const int kb0 = (tk.x >> 13) & 127, nkb = (tk.x >> 20) & 127, part = tk.x >> 28;
        const bool half = part && !shareA;
        const int blk = ((tk.x >> 4) & 15) + (shareA || half ? 0 : rank);
        const int nt = ((tk.x >> 8) & 31) + (shareA ? rank : 0);
        const CUtensorMap *ma, *mb, *mb2;
        int bcol, bcol2;
        if (type == T_A) { ma = &P.m[M_XN]; mb = mb2 = &P.m[nt < 16 ? M_WK : M_WV]; bcol = (nt & 15) * 256; bcol2 = bcol + 128; }
        else if (type == T_B) { ma = &P.m[M_XN]; mb = mb2 = &P.m[M_WQ]; bcol = nt * 256; bcol2 = bcol + 128; }
        else if (type == T_C) { ma = &P.m[M_XN]; mb = &P.m[M_WG]; mb2 = &P.m[M_WU]; bcol = bcol2 = nt * 128; }
        else if (type == T_E) { ma = &P.m[M_H]; mb = mb2 = &P.m[M_WD]; bcol = nt * 256; bcol2 = bcol + 128; }
        else { ma = &P.m[M_O]; mb = mb2 = &P.m[M_WO]; bcol = nt * 256; bcol2 = bcol + 128; }
        if (!shareA && rank) { mb = mb2; bcol = bcol2; }
        int ib = kb0;
        uint32_t sa_ = st;
        const int pre = type == T_D ? kb0 + NSTAGE : kb0 + 1;
#pragma unroll 1
        for (int kb = kb0; kb < kb0 + nkb; kb++) {
#pragma unroll 1
            for (const int lim = min(max(pre, kb + 1), kb0 + nkb); ib < lim; ib++) {
                mbar_wait_cl(sb + B_EMPTY + st * 8, ph);
                const uint32_t fb = sb + B_FULL + st * 8, sbb = sb + st * STAGE_BYTES + 16384;
                mbar_expect(fb, half ? STAGE_BYTES - 8192 : STAGE_BYTES);
                if (!shareA) {
                    tma2d_mc(sbb + rank * 16384, mb, bcol, ib * 64, fb);
                    tma2d_mc(sbb + rank * 16384 + 8192, mb, bcol + 64, ib * 64, fb);
                } else {
                    tma2d(sbb, mb, bcol, ib * 64, fb);
                    tma2d(sbb + 8192, mb, bcol + 64, ib * 64, fb);
                    tma2d(sbb + 16384, mb2, bcol2, ib * 64, fb);
                    tma2d(sbb + 24576, mb2, bcol2 + 64, ib * 64, fb);
                }
                if (++st == NSTAGE) { st = 0; ph ^= 1; }
            }
            const uint32_t fb = sb + B_FULL + sa_ * 8, sa = sb + sa_ * STAGE_BYTES;
            if (kb == kb0) {
                if (type <= T_C) wait_cnt(&g_sync.ln[blk], (E + 1) * 64);
                else wait_cnt(&g_sync.ai[blk], (E + 1) * 8);
                if (type == T_E) wait_cnt(&g_sync.hc[blk], (E + 1) * 88);
                fence_async_gl();
            }
            if (type == T_D && ((kb & 3) == 0 || kb == kb0)) { wait_cnt(&g_sync.oc[blk + (part >> 1) + (part == 3)][kb >> 2], (E + 1) * (part ? (part == 1 ? 4 : 2) : 8)); fence_async_gl(); }
            if (half) tma2d(sa, ma, kb * 64, blk * 128 + rank * 64, fb);
            else if (!shareA) {
                tma2d(sa, ma, kb * 64, blk * 128, fb);
                tma2d(sa + 8192, ma, kb * 64, blk * 128 + 64, fb);
            } else tma2d_mc(sa + rank * 8192, ma, kb * 64, blk * 128 + rank * 64, fb);
            sa_ = (sa_ + 1) & (NSTAGE - 1);
        }
        if (type == T_B) {
            wait_cnt(&g_sync.kv[blk][nt], (E + 1) * 8);
            wait_cnt(&g_sync.kv[blk][16 + nt], (E + 1) * 8);
            fence_async_gl();
#pragma unroll 1
            for (int x = 0; x < 4; x++) {
                mbar_wait_cl(sb + B_EMPTY + st * 8, ph);
                const uint32_t fb = sb + B_FULL + st * 8, sa = sb + st * STAGE_BYTES;
                mbar_expect(fb, 32768);
                const int c = (x >> 1) * 4096 + nt * 256 + (x & 1) * 128;
                tma2d(sa, &P.m[M_KVL], c, blk * 128, fb);
                tma2d(sa + 8192, &P.m[M_KVL], c, blk * 128 + 64, fb);
                tma2d(sa + 16384, &P.m[M_KVL], c + 64, blk * 128, fb);
                tma2d(sa + 24576, &P.m[M_KVL], c + 64, blk * 128 + 64, fb);
                if (++st == NSTAGE) { st = 0; ph ^= 1; }
            }
        }
    }
}

DEV void flush_flag(unsigned*& pend, int lane) {
    if (lane == 0 && pend) {
        bulk_wait_all(); fence_async_gl(); fence_gpu(); red_add(pend, 1);
        pend = nullptr;
    }
}
template <typename F>
DEV void store_box(F val, uint32_t slot, uint32_t soff, const CUtensorMap* m, int c0, int c1, int lane) {
    if (lane == 0) bulk_wait_read<1>();
    __syncwarp();
#pragma unroll
    for (int jj = 0; jj < 4; jj++)
        stm4(slot + (soff ^ (jj << 5)), val(8 * jj + 0), val(8 * jj + 2), val(8 * jj + 4), val(8 * jj + 6));
    fence_async_smem();
    __syncwarp();
    if (lane == 0) { tma_store(m, c0, c1, slot); bulk_commit(); }
}

DEV void convert_rows(const Params& P, int row0, int nt, int lane) {
    const float* ap = g_acc + (size_t)row0 * DM + nt * 256 + lane * 4;
    uint2* op = (uint2*)(P.out + (size_t)row0 * DM + nt * 256 + lane * 4);
    uint4 v[32];
#pragma unroll
    for (int i = 0; i < 32; i++) v[i] = ld_rlx4(ap + (i >> 1) * DM + (i & 1) * 128);
#pragma unroll
    for (int i = 0; i < 32; i++)
        op[(i >> 1) * (DM / 4) + (i & 1) * 32] = make_uint2(pk(__uint_as_float(v[i].x), __uint_as_float(v[i].y)), pk(__uint_as_float(v[i].z), __uint_as_float(v[i].w)));
}

DEV void bulk_consumer(const Params& P, uint32_t sb, uint32_t rank, unsigned E, int cw, int lane) {
    const int g = lane >> 2, t = lane & 3;
    uint32_t st = 0, ph = 0;
    const uint32_t tempty0 = mapa(sb + B_TEMPTY, 0);
    const uint32_t empty_a = mapa(sb + B_EMPTY, lane & 1);
    const uint64_t da0 = mkdesc(sb + (cw >> 2) * 8192, 16, 1024, 1), db0 = mkdesc(sb + 16384, 8192, 1024, 1);
    const uint32_t stg = sb + SM_STAGING + cw * 4096;
    const int srow = (lane & 7) + ((lane >> 3) & 1) * 8;
    const uint32_t soff = srow * 128 + (((lane >> 4) ^ (srow & 7)) << 4);
    unsigned* pend = nullptr;
#pragma unroll 1
    for (int n = 0;; n++) {
        float acc[128];
        mbar_wait_cl(sb + B_TFULL + (n & 1) * 8, (n >> 1) & 1);
        const uint32_t tx = lds1(sb + S_TASK + (n & 1) * 8), ty = lds1(sb + S_TASK + (n & 1) * 8 + 4);
        __syncwarp();
        const int type = tx & 7;
        bool hold = (type == T_B || type == T_D) && ((tx >> 4) & 15) >= HOLD;
        {
            const int pt = tx >> 28;
            if (pt && (pt == 1 ? cw >= 4 : pt != (cw >> 1))) hold = false;
        }
        if (lane == 0 && !hold) mbar_arrive_cl(tempty0 + (n & 1) * 8);
        if (type == T_END) break;
        const int shareA = (tx >> 3) & 1;
        const int part = tx >> 28;
        const bool half = part && !shareA;
        const int blk = ((tx >> 4) & 15) + (shareA || half ? 0 : rank);
        const int nt = ((tx >> 8) & 31) + (shareA ? rank : 0);
        const int nkb = (tx >> 20) & 127;
        const int urgent = (tx >> 27) & 1;
        if (part && (part == 1) == (cw >= 4)) {
#pragma unroll 1
            for (int kb = 0; kb < nkb; kb++) {
                mbar_wait(sb + B_FULL + st * 8, ph);
                if (lane < 2) mbar_arrive_cl(empty_a + st * 8);
                if (++st == NSTAGE) { st = 0; ph ^= 1; }
            }
            continue;
        }
        uint32_t pst = 0;
#pragma unroll
        for (int i = 0; i < 128; i++) acc[i] = 0.f;
#pragma unroll 1
        for (int kb = 0; kb < nkb; kb++) {
            if (!mbar_try(sb + B_FULL + st * 8, ph)) {
                flush_flag(pend, lane);
                mbar_wait(sb + B_FULL + st * 8, ph);
            }
            wg_fence();
            const uint64_t da = da0 + st * (STAGE_BYTES >> 4), db = db0 + st * (STAGE_BYTES >> 4);
            wgmma256(acc, da, db, 1);
            wgmma256(acc, da + 2, db + 128, 1);
            wgmma256(acc, da + 4, db + 256, 1);
            wgmma256(acc, da + 6, db + 384, 1);
            wg_commit();
            if (kb > 0) {
                wg_wait<1>();
                if (lane < 2) mbar_arrive_cl(empty_a + pst * 8);
                if (kb == 2) flush_flag(pend, lane);
            }
            pst = st;
            if (++st == NSTAGE) { st = 0; ph ^= 1; }
        }
        wg_wait<0>();
        if (lane < 2) mbar_arrive_cl(empty_a + pst * 8);
        flush_flag(pend, lane);
        const int row0 = blk * 128 + cw * 16 + (half ? rank * 64 : 0);
        if (type == T_B) {
            uint32_t qa[64];
#pragma unroll
            for (int i = 0; i < 64; i++) qa[i] = pk(acc[2 * i], acc[2 * i + 1]);
            const int hi = cw & 1, sl = cw >> 1, seg = blk * 4 + sl;
            const int rd = sl * 32 + hi * 16, rf = sl * 32;
            uint32_t pa[2][4][2];
            float ms[2][2], ls[2][2];
#pragma unroll
            for (int hh = 0; hh < 2; hh++) {
                float s[4][4];
#pragma unroll
                for (int i = 0; i < 4; i++) { s[i][0] = s[i][1] = s[i][2] = s[i][3] = 0.f; }
                mbar_wait(sb + B_FULL + st * 8, ph);
                const uint32_t kbase = sb + st * STAGE_BYTES;
#pragma unroll
                for (int tl = 0; tl < 4; tl++) {
                    if (tl < 2 || hi) {
                        const int R = (tl < 2 ? rd : rf) + (tl & 1) * 8 + (lane & 7);
#pragma unroll
                        for (int qq = 0; qq < 4; qq++) {
                            uint32_t kf[4];
                            ldm4(kf, kbase + (qq >> 1) * 16384 + R * 128 + (((((qq & 1) * 4) + (lane >> 3)) ^ (lane & 7)) << 4));
                            const uint32_t* q = qa + hh * 32 + qq * 8;
                            mma16(s[tl], q[0], q[1], q[2], q[3], kf[0], kf[1]);
                            mma16(s[tl], q[4], q[5], q[6], q[7], kf[2], kf[3]);
                        }
                    }
                }
                __syncwarp();
                if (lane < 2) mbar_arrive_cl(empty_a + st * 8);
                if (++st == NSTAGE) { st = 0; ph ^= 1; }
                const float NINF = __int_as_float(0xff800000);
                if (2 * t > g) { s[0][0] = NINF; s[1][2] = NINF; }
                if (2 * t + 1 > g) { s[0][1] = NINF; s[1][3] = NINF; }
                s[1][0] = NINF; s[1][1] = NINF;
                if (!hi) {
#pragma unroll
                    for (int i = 0; i < 4; i++) { s[2][i] = NINF; s[3][i] = NINF; }
                }
                float m0 = fmaxf(s[0][0], s[0][1]), m1 = fmaxf(s[0][2], s[0][3]);
#pragma unroll
                for (int i = 1; i < 4; i++) { m0 = fmaxf(m0, fmaxf(s[i][0], s[i][1])); m1 = fmaxf(m1, fmaxf(s[i][2], s[i][3])); }
                m0 = fmaxf(m0, __shfl_xor_sync(~0u, m0, 1)); m1 = fmaxf(m1, __shfl_xor_sync(~0u, m1, 1));
                m0 = fmaxf(m0, __shfl_xor_sync(~0u, m0, 2)); m1 = fmaxf(m1, __shfl_xor_sync(~0u, m1, 2));
                ms[hh][0] = m0; ms[hh][1] = m1;
                m0 *= -SCALE_LOG2E; m1 *= -SCALE_LOG2E;
                float l0 = 0.f, l1 = 0.f;
#pragma unroll
                for (int i = 0; i < 4; i++) {
                    float a = ex2(fmaf(s[i][0], SCALE_LOG2E, m0)), b = ex2(fmaf(s[i][1], SCALE_LOG2E, m0));
                    float c = ex2(fmaf(s[i][2], SCALE_LOG2E, m1)), d = ex2(fmaf(s[i][3], SCALE_LOG2E, m1));
                    l0 += a + b; l1 += c + d;
                    pa[hh][i][0] = pk(a, b); pa[hh][i][1] = pk(c, d);
                }
                ls[hh][0] = l0; ls[hh][1] = l1;
            }
            float o[64];
            auto pv_seg = [&](const uint32_t (&p)[4][2]) {
#pragma unroll
                for (int i = 0; i < 64; i++) o[i] = 0.f;
                mbar_wait(sb + B_FULL + st * 8, ph);
                const uint32_t vbase = sb + st * STAGE_BYTES;
#pragma unroll
                for (int pass = 0; pass < 2; pass++) {
                    if (pass == 0 || hi) {
                        const int R = (pass == 0 ? rd : rf) + (lane & 15);
#pragma unroll
                        for (int nn = 0; nn < 8; nn++) {
                            uint32_t vf[4];
                            ldm4t(vf, vbase + (nn >> 2) * 16384 + R * 128 + (((((nn & 3) * 2) + (lane >> 4)) ^ (lane & 7)) << 4));
                            mma16(o + 8 * nn, p[2 * pass][0], p[2 * pass][1], p[1 + 2 * pass][0], p[1 + 2 * pass][1], vf[0], vf[1]);
                            mma16(o + 8 * nn + 4, p[2 * pass][0], p[2 * pass][1], p[1 + 2 * pass][0], p[1 + 2 * pass][1], vf[2], vf[3]);
                        }
                    }
                }
                __syncwarp();
                if (lane < 2) mbar_arrive_cl(empty_a + st * 8);
                if (++st == NSTAGE) { st = 0; ph ^= 1; }
            };
            pv_seg(pa[0]);
            if (lane < 4) wait_cnt(&g_sync.prog[nt * 4 + lane][0], E * 64 + seg + 1, WSP);
            __syncwarp();
            const uint4* kvm = g_kvm + (seg * NH + nt * 2) * 256 + lane;
            if (lane == 0 && hold) mbar_arrive_cl(tempty0 + (n & 1) * 8);
            uint4 vm[4];
            uint32_t pm[2][2];
            float cs[2][2];
            {
                uint4 km[8];
#pragma unroll
                for (int i = 0; i < 8; i++) km[i] = ld_rlx4(kvm + (i >> 2) * 256 + (i & 3) * 32);
#pragma unroll
                for (int i = 0; i < 4; i++) vm[i] = ld_rlx4(kvm + 128 + i * 32);
#pragma unroll
                for (int hh = 0; hh < 2; hh++) {
                    float s[4] = {0.f, 0.f, 0.f, 0.f}, s2[4] = {0.f, 0.f, 0.f, 0.f};
#pragma unroll
                    for (int i = 0; i < 4; i++) {
                        const uint32_t* q = qa + hh * 32 + i * 8;
                        mma16(s, q[0], q[1], q[2], q[3], km[hh * 4 + i].x, km[hh * 4 + i].y);
                        mma16(s2, q[4], q[5], q[6], q[7], km[hh * 4 + i].z, km[hh * 4 + i].w);
                    }
#pragma unroll
                    for (int i = 0; i < 4; i++) s[i] += s2[i];
                    float m0 = fmaxf(s[0], s[1]), m1 = fmaxf(s[2], s[3]);
                    m0 = fmaxf(m0, __shfl_xor_sync(~0u, m0, 1)); m1 = fmaxf(m1, __shfl_xor_sync(~0u, m1, 1));
                    m0 = fmaxf(m0, __shfl_xor_sync(~0u, m0, 2)); m1 = fmaxf(m1, __shfl_xor_sync(~0u, m1, 2));
                    m0 = fmaxf(m0, ms[hh][0]); m1 = fmaxf(m1, ms[hh][1]);
                    const float c0 = ex2((ms[hh][0] - m0) * SCALE_LOG2E), c1 = ex2((ms[hh][1] - m1) * SCALE_LOG2E);
                    m0 *= -SCALE_LOG2E; m1 *= -SCALE_LOG2E;
                    const float a = ex2(fmaf(s[0], SCALE_LOG2E, m0)), b = ex2(fmaf(s[1], SCALE_LOG2E, m0));
                    const float c = ex2(fmaf(s[2], SCALE_LOG2E, m1)), d = ex2(fmaf(s[3], SCALE_LOG2E, m1));
                    float l0 = fmaf(ls[hh][0], c0, a + b), l1 = fmaf(ls[hh][1], c1, c + d);
                    pm[hh][0] = pk(a, b); pm[hh][1] = pk(c, d);
                    l0 += __shfl_xor_sync(~0u, l0, 1); l1 += __shfl_xor_sync(~0u, l1, 1);
                    l0 += __shfl_xor_sync(~0u, l0, 2); l1 += __shfl_xor_sync(~0u, l1, 2);
                    ls[hh][0] = __fdividef(1.f, l0); ls[hh][1] = __fdividef(1.f, l1);
                    cs[hh][0] = c0; cs[hh][1] = c1;
                }
            }
#pragma unroll
            for (int hh = 0; hh < 2; hh++) {
                uint4 vn[4];
                if (hh == 0) {
#pragma unroll
                    for (int i = 0; i < 4; i++) vn[i] = ld_rlx4(kvm + 384 + i * 32);
                } else {
                    pv_seg(pa[1]);
                }
#pragma unroll
                for (int i = 0; i < 64; i++) o[i] *= cs[hh][(i >> 1) & 1];
#pragma unroll
                for (int i = 0; i < 4; i++) {
                    mma8(o + 16 * i, pm[hh][0], pm[hh][1], movm(vm[i].x));
                    mma8(o + 16 * i + 4, pm[hh][0], pm[hh][1], movm(vm[i].y));
                    mma8(o + 16 * i + 8, pm[hh][0], pm[hh][1], movm(vm[i].z));
                    mma8(o + 16 * i + 12, pm[hh][0], pm[hh][1], movm(vm[i].w));
                }
                __syncwarp();
#pragma unroll
                for (int b = 0; b < 2; b++)
#pragma unroll
                    for (int jj = 0; jj < 4; jj++) {
                        const float* q = o + 32 * b + 8 * jj;
                        stm4(stg + b * 2048 + (soff ^ (jj << 5)), pk(q[0] * ls[hh][0], q[1] * ls[hh][0]), pk(q[2] * ls[hh][1], q[3] * ls[hh][1]),
                             pk(q[4] * ls[hh][0], q[5] * ls[hh][0]), pk(q[6] * ls[hh][1], q[7] * ls[hh][1]));
                    }
                __syncwarp();
#pragma unroll
                for (int i = 0; i < 8; i++) {
                    const int r = (i & 3) * 4 + (lane >> 3), c = lane & 7;
                    const uint4 v = lds4(stg + (i >> 2) * 2048 + r * 128 + ((c ^ (r & 7)) << 4));
                    *(uint4*)(g_o + (size_t)(row0 + r) * 4096 + nt * 256 + hh * 128 + (i >> 2) * 64 + c * 8) = v;
                }
                if (hh == 0) {
#pragma unroll
                    for (int i = 0; i < 4; i++) vm[i] = vn[i];
                }
            }
            __syncwarp();
            if (lane == 0) { fence_gpu(); red_add(&g_sync.oc[blk == 15 && cw >= 4 ? 14 + (cw >> 1) : blk][nt], 1); }
        } else if (type == T_A) {
#pragma unroll
            for (int b = 0; b < 4; b++)
                store_box([&](int i) { return pk(acc[32 * b + i], acc[32 * b + i + 1]); }, stg + (b & 1) * 2048, soff, &P.m[M_SKV],
                          nt * 256 + b * 64, row0, lane);
            pend = &g_sync.kv[blk][nt];
        } else if (type == T_C) {
#pragma unroll
            for (int b = 0; b < 2; b++)
                store_box([&](int i) { return pk(acc[32 * b + i] * acc[64 + 32 * b + i], acc[32 * b + i + 1] * acc[64 + 32 * b + i + 1]); },
                          stg + (b & 1) * 2048, soff, &P.m[M_SH], nt * 128 + b * 64, row0, lane);
            pend = &g_sync.hc[blk];
        } else
        if (part < 2 || part == (cw >> 1)) {
            if (lane == 0) fence_async_gl();
            const uint32_t so = g * 128 + (t & 1) * 8;
#pragma unroll
            for (int b = 0; b < 8; b++) {
                const uint32_t slot = stg + (b & 1) * 2048;
                if (lane == 0) bulk_wait_read<1>();
                __syncwarp();
#pragma unroll
                for (int j = 0; j < 4; j++) {
                    const uint32_t a = slot + so + (((2 * j + (t >> 1)) ^ g) << 4);
                    sts2f(a, acc[16 * b + 4 * j], acc[16 * b + 4 * j + 1]);
                    sts2f(a + 1024, acc[16 * b + 4 * j + 2], acc[16 * b + 4 * j + 3]);
                }
                fence_async_smem();
                __syncwarp();
                if (lane == 0) { tma_reduce(&P.m[M_RACC], nt * 256 + b * 32, row0, slot); bulk_commit(); }
            }
            if (lane == 0 && hold) mbar_arrive_cl(tempty0 + (n & 1) * 8);
            unsigned old = 0;
            if (lane == 0) { bulk_wait_all(); fence_async_gl(); old = atom_ar(&g_sync.dc[blk][nt][cw]); }
            old = __shfl_sync(~0u, old, 0);
            if (old + 1 == (E + 1) * ((cw >= 4 ? ty >> 8 : ty) & 255)) {
                convert_rows(P, row0, nt, lane);
            }
        }
        if (urgent) flush_flag(pend, lane);
    }
    flush_flag(pend, lane);
    if (lane == 0) bulk_wait_all();
    __syncwarp();
}

__global__ void __cluster_dims__(2, 1, 1) __launch_bounds__(NTHREADS, 1) fused_kernel(const __grid_constant__ Params P) {
    extern __shared__ __align__(1024) unsigned char smem[];
    const uint32_t sb = smem_u32(smem);
    const int tid = threadIdx.x, lane = tid & 31, warp = __shfl_sync(~0u, tid >> 5, 0);
    const unsigned t_start = clk32();
    uint32_t rank;
    asm volatile("mov.u32 %0, %%cluster_ctarank;" : "=r"(rank));
    if (tid == INITT) {
        if ((sb & 2047) != 1024) __trap();
        for (int i = 0; i < NSTAGE; i++) { mbar_init(sb + B_FULL + i * 8, 1); mbar_init(sb + B_EMPTY + i * 8, 16); }
        for (int i = 0; i < 2; i++) { mbar_init(sb + B_TFULL + i * 8, 1); mbar_init(sb + B_TEMPTY + i * 8, 17); }
        mbar_init(sb + B_ROLE, 1);
        sts1(sb + S_FLAG, 0);
        for (int i = 0; i < 4; i++) mbar_init(sb + B_KV + i * 8, 1);
        mbar_init(sb + B_S, 1); mbar_init(sb + B_VL, 2); mbar_init(sb + B_VR, 1); mbar_init(sb + B_P, 1); mbar_init(sb + B_G, 1);
        asm volatile("fence.mbarrier_init.release.cluster;" ::: "memory");
    }
    __syncwarp();
    cluster_arrive();
    if (warp < 4) {
        asm volatile("setmaxnreg.dec.sync.aligned.u32 56;");
        if (rank == 1 && warp == 3) {
            l2_line(P.pg[lane]); l2_line(P.pg[32 + lane]);
            l2_line((const char*)&g_sync + lane * 128); l2_line((const char*)&g_sync + 4096 + lane * 128);
            l2_line((const char*)g_tasks + lane * 128);
            if (lane < (NTASK * 8 - 4096 + 127) / 128) l2_line((const char*)g_tasks + 4096 + lane * 128);
        }
        if (warp == 3 && lane < M_COUNT) asm volatile("prefetch.tensormap [%0];" ::"l"(&P.m[lane]) : "memory");
        if (rank == 0 && lane == 0) {
            unsigned ep = 0;
            if (warp == 2) ep = atomicAdd(&g_sync.start, 1);
            unsigned best = 1u << 30;
            unsigned* p = (unsigned*)(P.arena + (5 << 18) + (1 << 16) + ((warp ^ 1 ^ (warp >> 1)) & 1) * 4096 + (warp >> 1) * 8192 + ((blockIdx.x >> 1) & 31) * 128);
#pragma unroll 1
            for (int r = 0; r < NPROBE; r++) {
                unsigned t0 = clk32(), v;
                asm volatile("atom.relaxed.gpu.global.add.u32 %0, [%1], 0;" : "=r"(v) : "l"(p) : "memory");
                if (v == 0x12345678u) __trap();
                best = min(best, clk32() - t0);
            }
            sts1(sb + S_PROBE + warp * 4, best);
            if (warp == 2) sts1(sb + S_PROBE + 16, ep / NPAIR);
        }
        __syncwarp();
        bar_sync(7, 128);
        cluster_wait();
        if (rank == 0 && tid == 0) {
            const unsigned E = lds1(sb + S_PROBE + 16);
            const int side = min(lds1(sb + S_PROBE + 4), lds1(sb + S_PROBE + 12)) < min(lds1(sb + S_PROBE), lds1(sb + S_PROBE + 8));
            if (blockIdx.x == 0) { g_sync.tick[(E + 2) & 3][0] = 0; g_sync.tick[(E + 2) & 3][1] = 0; g_sync.task[(E + 2) & 3] = 0; }
            unsigned tk = atomicAdd(&g_sync.tick[E & 3][side], 1);
            int role;
            if (side == 1) role = tk < 32 ? (int)tk : (int)tk - NPAIR;
            else {
                long long t0 = clock64();
                unsigned n0, n1;
                while (true) {
                    n1 = ld_rlx(&g_sync.tick[E & 3][1]); n0 = ld_rlx(&g_sync.tick[E & 3][0]);
                    if (n1 >= 32 || n0 + n1 >= NPAIR) break;
                    if (clock64() - t0 > TIMEOUT) __trap();
                }
                const int d = n1 < 32 ? 32 - n1 : 0;
                role = (int)tk < d ? (int)(n1 + tk) : d - 1 - (int)tk;
            }
            bcast2(sb + S_ROLE, sb + B_ROLE, (uint32_t)role, E);
        }
        __syncwarp();
        mbar_wait_cl(sb + B_ROLE, 0);
        const int role = (int)lds1(sb + S_ROLE);
        const unsigned E = lds1(sb + S_ROLE + 4);
        if (role >= 0) {
            chain_helper(P, sb, role, rank, E, warp, lane);
            fence_async_all();
            cluster_arrive(); cluster_wait();
        }
        else if (warp == 1 || warp == 2) {
            const int w = (-1 - role) * 4 + rank * 2 + warp - 1;
            if (w < 128) {
                delay(t_start, 30000);
                const uint2* src = (const uint2*)(P.x + (size_t)w * 16 * DM) + lane;
                float4* dst = (float4*)(g_acc + (size_t)w * 16 * DM) + lane;
#pragma unroll 8
                for (int i = 0; i < 64; i++) { const uint2 v = __ldg(src + i * 32); dst[i * 32] = make_float4(blo(v.x), bhi(v.x), blo(v.y), bhi(v.y)); }
                fence_async_gl();
                __syncwarp();
                if (lane == 0) { fence_gpu(); red_add(&g_sync.ai[w >> 3], 1); }
            }
        }
        if (tid == 0) bulk_producer(P, sb, rank, lds1v(sb + S_ROLE + 4), -1 - (int)lds1v(sb + S_ROLE));
        __syncwarp();
        cluster_arrive(); cluster_wait();
    } else {
        asm volatile("setmaxnreg.inc.sync.aligned.u32 224;");
        const int cw = warp - 4;
        if (blockIdx.x < 128) {
            const int row = blockIdx.x * 16 + cw * 2;
            uint4 v[2][2];
#pragma unroll
            for (int r = 0; r < 2; r++) {
                const uint4* p = (const uint4*)(P.x + (size_t)(row + r) * DM);
                v[r][0] = __ldg(p + lane); v[r][1] = __ldg(p + 32 + lane);
            }
#pragma unroll
            for (int r = 0; r < 2; r++) {
                float f[16];
                const uint32_t w[8] = {v[r][0].x, v[r][0].y, v[r][0].z, v[r][0].w, v[r][1].x, v[r][1].y, v[r][1].z, v[r][1].w};
                float s = 0.f;
#pragma unroll
                for (int i = 0; i < 8; i++) { f[2 * i] = __uint_as_float(w[i] << 16); f[2 * i + 1] = __uint_as_float(w[i] & 0xffff0000u); s += f[2 * i] + f[2 * i + 1]; }
#pragma unroll
                for (int o = 16; o; o >>= 1) s += __shfl_xor_sync(~0u, s, o);
                const float mean = s * (1.f / DM);
                float q = 0.f;
#pragma unroll
                for (int i = 0; i < 16; i++) { f[i] -= mean; q += f[i] * f[i]; }
#pragma unroll
                for (int o = 16; o; o >>= 1) q += __shfl_xor_sync(~0u, q, o);
                const float rs = rsqrtf(q * (1.f / DM) + 1e-5f);
                uint4* d = (uint4*)(g_xn + (size_t)(row + r) * DM);
                d[lane] = make_uint4(pk(f[0] * rs, f[1] * rs), pk(f[2] * rs, f[3] * rs), pk(f[4] * rs, f[5] * rs), pk(f[6] * rs, f[7] * rs));
                d[32 + lane] = make_uint4(pk(f[8] * rs, f[9] * rs), pk(f[10] * rs, f[11] * rs), pk(f[12] * rs, f[13] * rs), pk(f[14] * rs, f[15] * rs));
            }
            fence_async_gl();
            __syncwarp();
            if (lane == 0) { fence_gpu(); red_add(&g_sync.ln[row >> 7], 1); }
        }
        cluster_wait();
        mbar_wait_cl(sb + B_ROLE, 0);
        sts1(sb + S_PH + cw * 4, (int)lds1(sb + S_ROLE) >= 0 ? 0 : 1);
#pragma unroll 1
        while (true) {
            __syncwarp();
            const int phase = lds1(sb + S_PH + cw * 4), role = (int)lds1(sb + S_ROLE);
            const unsigned E = lds1(sb + S_ROLE + 4);
            __syncwarp();
            sts1(sb + S_PH + cw * 4, phase + 1);
            if (phase == 0) {
                chain_compute(P, sb, role, rank, E, cw, __shfl_sync(~0u, lane, lane));
                fence_async_all();
                cluster_arrive(); cluster_wait();
            } else if (phase == 1) {
                bulk_consumer(P, sb, rank, E, cw, __shfl_sync(~0u, lane, lane));
            } else break;
        }
        cluster_arrive(); cluster_wait();
    }
}

typedef CUresult (*EncodeFn)(CUtensorMap*, CUtensorMapDataType, cuuint32_t, void*, const cuuint64_t*, const cuuint64_t*, const cuuint32_t*,
                             const cuuint32_t*, CUtensorMapInterleave, CUtensorMapSwizzle, CUtensorMapL2promotion, CUtensorMapFloatOOBfill);

static void map2d(EncodeFn fn, CUtensorMap* m, const void* base, uint64_t cols, uint64_t rows, uint32_t bc, uint32_t br) {
    cuuint64_t dims[2] = {cols, rows};
    cuuint64_t strides[1] = {cols * 2};
    cuuint32_t box[2] = {bc, br}, es[2] = {1, 1};
    fn(m, CU_TENSOR_MAP_DATA_TYPE_BFLOAT16, 2, (void*)base, dims, strides, box, es, CU_TENSOR_MAP_INTERLEAVE_NONE, CU_TENSOR_MAP_SWIZZLE_128B,
       CU_TENSOR_MAP_L2_PROMOTION_L2_256B, CU_TENSOR_MAP_FLOAT_OOB_FILL_NONE);
}
extern "C" void kernel_launch(void* const* d_in, const int* in_sizes, int n_in, void* d_out, int out_size) {
    static Params P;
    static const void* key[12];
    static bool ready = false;
    bool same = ready && key[11] == d_out;
    for (int i = 0; i < 11 && same; i++) same = key[i] == d_in[i];
    if (!same) {
        void* fp = nullptr;
        cudaDriverEntryPointQueryResult qr;
        cudaGetDriverEntryPoint("cuTensorMapEncodeTiled", &fp, cudaEnableDefault, &qr);
        EncodeFn fn = (EncodeFn)fp;
        void *xn, *kv, *o, *h, *ar;
        cudaGetSymbolAddress(&ar, g_arena);
        P.arena = (char*)(((uintptr_t)ar + (2u << 20) - 1) & ~(uintptr_t)((2u << 20) - 1));
        cudaGetSymbolAddress(&xn, g_xn); cudaGetSymbolAddress(&kv, g_kv); cudaGetSymbolAddress(&o, g_o); cudaGetSymbolAddress(&h, g_h);
        map2d(fn, &P.m[M_XN], xn, DM, SEQ, 64, 64);
        map2d(fn, &P.m[M_H], h, FF, SEQ, 64, 64);
        map2d(fn, &P.m[M_O], o, 4096, SEQ, 64, 64);
        map2d(fn, &P.m[M_KVL], kv, 8192, SEQ, 64, 64);
        map2d(fn, &P.m[M_WQ], d_in[2], 4096, DM, 64, 64);
        map2d(fn, &P.m[M_WK], d_in[3], 4096, DM, 64, 64);
        map2d(fn, &P.m[M_WV], d_in[4], 4096, DM, 64, 64);
        map2d(fn, &P.m[M_WG], d_in[8], FF, DM, 64, 64);
        map2d(fn, &P.m[M_WU], d_in[9], FF, DM, 64, 64);
        map2d(fn, &P.m[M_WD], d_in[10], DM, FF, 64, 64);
        map2d(fn, &P.m[M_WO], d_in[5], DM, 4096, 64, 64);
        map2d(fn, &P.m[M_KVC], kv, 8192, SEQ, 64, 32);
        map2d(fn, &P.m[M_SKV], kv, 8192, SEQ, 64, 16);
        map2d(fn, &P.m[M_SO], o, 4096, SEQ, 64, 16);
        map2d(fn, &P.m[M_SH], h, FF, SEQ, 64, 16);
        {
            void* ac;
            cudaGetSymbolAddress(&ac, g_acc);
            cuuint64_t dims[2] = {DM, SEQ}, strides[1] = {DM * 4};
            cuuint32_t box[2] = {32, 16}, es[2] = {1, 1};
            fn(&P.m[M_RACC], CU_TENSOR_MAP_DATA_TYPE_FLOAT32, 2, ac, dims, strides, box, es, CU_TENSOR_MAP_INTERLEAVE_NONE, CU_TENSOR_MAP_SWIZZLE_128B,
               CU_TENSOR_MAP_L2_PROMOTION_NONE, CU_TENSOR_MAP_FLOAT_OOB_FILL_NONE);
        }
        P.x = (const __nv_bfloat16*)d_in[0];
        P.mem0 = (const __nv_bfloat16*)d_in[1];
        P.w[0] = (const __nv_bfloat16*)d_in[3]; P.w[1] = (const __nv_bfloat16*)d_in[4];
        P.w[2] = (const __nv_bfloat16*)d_in[2]; P.w[3] = (const __nv_bfloat16*)d_in[5];
        P.out = (__nv_bfloat16*)d_out;
        {
            void *ac, *km;
            cudaGetSymbolAddress(&ac, g_acc); cudaGetSymbolAddress(&km, g_kvm);
            const void* b[14] = {xn, ac, kv, km, d_in[3], d_in[4], d_in[2], d_in[5], d_in[8], d_in[9], h, d_in[10], o, d_out};
            const size_t n[14] = {2, 4, 32, 8, 4, 4, 4, 4, 1, 1, 5, 1, 16, 2};
            int c = 0;
            for (int i = 0; i < 14; i++)
                for (size_t m = 0; m < n[i]; m += 2) {
                    if (c < 64) P.pg[c++] = (const char*)b[i] + (m << 20);
                    if (m + 2 >= n[i] && c < 64) P.pg[c++] = (const char*)b[i] + (n[i] << 20) - 128;
                }
            while (c < 64) P.pg[c++] = (const char*)xn;
        }
        cudaFuncSetAttribute(fused_kernel, cudaFuncAttributeMaxDynamicSharedMemorySize, SMEM_BYTES);
        for (int i = 0; i < 11; i++) key[i] = d_in[i];
        key[11] = d_out;
        ready = true;
    }
    fused_kernel<<<NCTA, NTHREADS, SMEM_BYTES, cudaStreamPerThread>>>(P);
}
```
